```python
import torch

def _softmax(x, axis=-1):
    return torch.softmax(x, dim=axis)
def _gelu(x):
    return torch.nn.functional.gelu(x, approximate="tanh")
def _silu(x):
    return torch.nn.functional.silu(x)
def _sigmoid(x):
    return torch.sigmoid(x)
def _layernorm(x, axis=-1, eps=1e-5):
    m = x.mean(dim=axis, keepdim=True)
    v = x.var(dim=axis, keepdim=True, unbiased=False)
    return (x - m) / torch.sqrt(v + eps)
def _scatter_add(tgt, idx, src, axis=0):
    return tgt.clone().index_add_(axis, idx, src)
def _segment_sum(src, seg, n):
    out = torch.zeros((n,) + src.shape[1:], dtype=src.dtype)
    return out.index_add_(0, seg, src)
def _pad(x, pw):
    flat = tuple(v for pair in reversed(pw) for v in pair)
    return torch.nn.functional.pad(x, flat)

kernel_name = 'recurrent_scan__gqa_block_cached__swiglu_ffn__decode'

def setup_inputs():

    _w = (lambda a: (lambda t: t.to(torch.bfloat16) if t.is_floating_point() else t)(torch.as_tensor(a)))
    def _A_setup():
        B, Sq, D = 8, 1, 576
        Hq, Hkv, Sk, Dh = 32, 16, 8192, 128
        assert Hq % Hkv == 0, (Hq, Hkv)
        return {
            "x": _w((lambda *s: torch.randn(*s, dtype=torch.bfloat16) * 0.05)(B, Sq, D)),
            "k_cache": _w((lambda *s: torch.randn(*s, dtype=torch.bfloat16) * 0.8)(B, Hkv, Sk, Dh)),
            "v_cache": _w((lambda *s: torch.randn(*s, dtype=torch.bfloat16) * 0.2)(B, Hkv, Sk, Dh)),
            "wq": _w((lambda *s: torch.randn(*s, dtype=torch.bfloat16) * 0.8)(D, Hq * Dh) * (D ** -0.5)),
            "wo": _w((lambda *s: torch.randn(*s, dtype=torch.bfloat16) * 0.2)(Hq * Dh, D) * ((Hq * Dh) ** -0.5)),
        }
    _A_in = _A_setup()

    def _B_setup():
        B, S, D, F = 8, 1, 576, 4608
        return {
            "x": _w((lambda *s: torch.randn(*s, dtype=torch.bfloat16) * 0.05)(B, S, D)),
            "w_gate": _w((lambda *s: torch.randn(*s, dtype=torch.bfloat16) * 0.1)(D, F)),
            "w_up": _w((lambda *s: torch.randn(*s, dtype=torch.bfloat16) * 0.1)(D, F)),
            "w_down": _w((lambda *s: torch.randn(*s, dtype=torch.bfloat16) * 0.1)(F, D)),
        }
    _B_in = _B_setup()

    return {
        "A_x": _A_in["x"],
        "A_k_cache": _A_in["k_cache"],
        "A_v_cache": _A_in["v_cache"],
        "A_wq": _A_in["wq"],
        "A_wo": _A_in["wo"],
        "B_x": _B_in["x"],
        "B_w_gate": _B_in["w_gate"],
        "B_w_up": _B_in["w_up"],
        "B_w_down": _B_in["w_down"],
    }

def reference(A_x, A_k_cache, A_v_cache, A_wq, A_wo, B_x, B_w_gate, B_w_up, B_w_down):
    def _A_ref(x, k_cache, v_cache, wq, wo):
        B, Sq, D = x.shape
        Hq, Dh = 32, 128
        Hkv = k_cache.shape[1]
        rep = Hq // Hkv
        q = (lambda x, *d: x.permute(*d))((x @ wq).reshape(B, Sq, Hq, Dh), 0, 2, 1, 3)
        k = (lambda x, n, axis: torch.repeat_interleave(x, n, dim=axis))(k_cache, rep, axis=1)
        v = (lambda x, n, axis: torch.repeat_interleave(x, n, dim=axis))(v_cache, rep, axis=1)
        scores = torch.einsum("bhqd,bhkd->bhqk", q, k) * (Dh ** -0.5)
        p = _softmax(scores, axis=-1)
        o = torch.einsum("bhqk,bhkd->bhqd", p, v)
        return (lambda x, *d: x.permute(*d))(o, 0, 2, 1, 3).reshape(B, Sq, Hq * Dh) @ wo

    def _B_ref(x, w_gate, w_up, w_down):
        g = _silu(x @ w_gate)
        u = x @ w_up
        return (g * u) @ w_down

    x = A_x
    xn = _layernorm(x, axis=-1)
    s = _A_ref(xn, A_k_cache, A_v_cache, A_wq, A_wo)
    g = _silu(_B_ref(xn, B_w_gate, B_w_up, B_w_down))
    return x + s * g
```

```cpp
#include <cuda_runtime.h>
#include <cuda_bf16.h>
#include <cuda.h>
#include <stdint.h>

namespace {

constexpr int kB = 8, kD = 576, kHKV = 16, kSK = 8192, kF = 4608;
constexpr int kPairs = kB * kHKV;
constexpr int kItemRows = 128;
constexpr int kItemsPerPair = kSK / kItemRows;
constexpr int kNAtt = kPairs * kItemsPerPair;
constexpr int kNFfn = kF / 32;
constexpr int kNItems = kNAtt + kNFfn;
#define KSLOTS 8
#define KINFL 3
#define KTAILITEMS 512
#define KCODEPF 0
#define KCODEBYTES 73728
#define KLASTFREE 0
#define KGATE7 64
constexpr int kSlots = KSLOTS;
static_assert(kSlots % 4 == 0, "a slot must always be consumed by the same warp (mbarrier phase safety)");
constexpr int kSlotBytes = 16384;
constexpr int kStaticItems = 1;
constexpr int kMaxCtas = 160;
constexpr int kSliceCtas = 128;
constexpr int kFinalCtas = 96;
constexpr int kThreads = 256;
constexpr int kOutElems = kB * kD;

constexpr int kOffRing = 0;
constexpr int kOffW = kOffRing + kSlots * kSlotBytes;
constexpr int kOffXn = kOffW + 36864;
constexpr int kXnPitch = 584;
constexpr int kOffMbuf = kOffXn + kB * kXnPitch * 2;
constexpr int kMbufStride = 264;
constexpr int kOffOs = kOffMbuf + 2 * 4 * kMbufStride * 4;
constexpr int kOffWbuf = kOffOs + 8 * 40 * 2;
constexpr int kOffFsum = kOffWbuf + 2 * 64 * 8;
constexpr int kOffSsum = kOffFsum + 10 * 48 * 4;
constexpr int kOffInfo = kOffSsum + 6 * 48 * 4;
constexpr int kOffBar = kOffInfo + 64;
constexpr int kNumBars = 3 * kSlots + 8;
constexpr int kSmemBytes = kOffBar + kNumBars * 8 + 1024;
static_assert(kSmemBytes <= 232448, "smem");

struct Counters {
  unsigned claim;
  unsigned qready; unsigned pad1[30];
  unsigned ddone;  unsigned pad2[31];
  unsigned zready; unsigned pad3[31];
  unsigned exitc;  unsigned pad4[31];
  unsigned done[kPairs * 32];
};

__device__ Counters g_ctr;
__device__ __align__(128) __nv_bfloat16 g_q[kPairs * 256];
__device__ __align__(128) float g_po[(size_t)kNAtt * 256];
__device__ __align__(128) float4 g_pml[kNAtt * 8];
__device__ __align__(128) float g_sp[kSliceCtas * kOutElems];
__device__ __align__(128) float g_dp[kMaxCtas * kOutElems];
#define TS(i)

#define KTRAP() __trap()
constexpr int kSpinLimit = 1 << 21;

__device__ __forceinline__ uint32_t smem_u32(const void* p) { return (uint32_t)__cvta_generic_to_shared(p); }
__device__ __forceinline__ void mbar_init(uint32_t bar, uint32_t cnt) {
  asm volatile("mbarrier.init.shared::cta.b64 [%0], %1;" ::"r"(bar), "r"(cnt) : "memory");
}
__device__ __forceinline__ void mbar_expect_tx(uint32_t bar, uint32_t bytes) {
  asm volatile("mbarrier.arrive.expect_tx.shared::cta.b64 _, [%0], %1;" ::"r"(bar), "r"(bytes) : "memory");
}
__device__ __forceinline__ void mbar_arrive(uint32_t bar) {
  asm volatile("mbarrier.arrive.shared::cta.b64 _, [%0];" ::"r"(bar) : "memory");
}
__device__ __forceinline__ void mbar_wait(uint32_t bar, uint32_t parity) {
  uint32_t done;
  int it = 0;
  do {
    asm volatile(
        "{\n.reg .pred p;\nmbarrier.try_wait.parity.shared::cta.b64 p, [%1], %2;\nselp.u32 %0, 1, 0, p;\n}"
        : "=r"(done) : "r"(bar), "r"(parity) : "memory");
    if (++it > kSpinLimit) KTRAP();
  } while (!done);
}
__device__ __forceinline__ void tma2d(uint32_t dst, const CUtensorMap* m, int c0, int c1, uint32_t bar, uint64_t pol) {
  asm volatile(
      "cp.async.bulk.tensor.2d.shared::cluster.global.mbarrier::complete_tx::bytes.L2::cache_hint [%0], [%1, {%3, %4}], [%2], %5;"
      ::"r"(dst), "l"(m), "r"(bar), "r"(c0), "r"(c1), "l"(pol) : "memory");
}
__device__ __forceinline__ void tma3d(uint32_t dst, const CUtensorMap* m, int c0, int c1, int c2, uint32_t bar, uint64_t pol) {
  asm volatile(
      "cp.async.bulk.tensor.3d.shared::cluster.global.mbarrier::complete_tx::bytes.L2::cache_hint [%0], [%1, {%3, %4, %5}], [%2], %6;"
      ::"r"(dst), "l"(m), "r"(bar), "r"(c0), "r"(c1), "r"(c2), "l"(pol) : "memory");
}
__device__ __forceinline__ void tma4d(uint32_t dst, const CUtensorMap* m, int c0, int c1, int c2, int c3, uint32_t bar, uint64_t pol) {
  asm volatile(
      "cp.async.bulk.tensor.4d.shared::cluster.global.mbarrier::complete_tx::bytes.L2::cache_hint [%0], [%1, {%3, %4, %5, %6}], [%2], %7;"
      ::"r"(dst), "l"(m), "r"(bar), "r"(c0), "r"(c1), "r"(c2), "r"(c3), "l"(pol) : "memory");
}
__device__ __forceinline__ void ldsm4(uint32_t (&r)[4], uint32_t addr) {
  asm volatile("ldmatrix.sync.aligned.m8n8.x4.shared.b16 {%0,%1,%2,%3}, [%4];"
               : "=r"(r[0]), "=r"(r[1]), "=r"(r[2]), "=r"(r[3]) : "r"(addr) : "memory");
}
__device__ __forceinline__ void ldsm4t(uint32_t (&r)[4], uint32_t addr) {
  asm volatile("ldmatrix.sync.aligned.m8n8.x4.trans.shared.b16 {%0,%1,%2,%3}, [%4];"
               : "=r"(r[0]), "=r"(r[1]), "=r"(r[2]), "=r"(r[3]) : "r"(addr) : "memory");
}
__device__ __forceinline__ void mma16816(float (&c)[4], const uint32_t (&a)[4], uint32_t b0, uint32_t b1) {
  asm(
      "mma.sync.aligned.m16n8k16.row.col.f32.bf16.bf16.f32 {%0,%1,%2,%3}, {%4,%5,%6,%7}, {%8,%9}, {%0,%1,%2,%3};"
      : "+f"(c[0]), "+f"(c[1]), "+f"(c[2]), "+f"(c[3])
      : "r"(a[0]), "r"(a[1]), "r"(a[2]), "r"(a[3]), "r"(b0), "r"(b1));
}
__device__ __forceinline__ uint32_t movmat(uint32_t a) {
  uint32_t d;
  asm volatile("movmatrix.sync.aligned.m8n8.trans.b16 %0, %1;" : "=r"(d) : "r"(a));
  return d;
}
__device__ __forceinline__ float ex2(float x) {
  float y;
  asm("ex2.approx.ftz.f32 %0, %1;" : "=f"(y) : "f"(x));
  return y;
}
__device__ __forceinline__ uint32_t pack_bf16(float lo, float hi) {
  uint32_t r;
  asm("cvt.rn.bf16x2.f32 %0, %1, %2;" : "=r"(r) : "f"(hi), "f"(lo));
  return r;
}
__device__ __forceinline__ float bf16r(float x) { return __bfloat162float(__float2bfloat16_rn(x)); }
__device__ __forceinline__ float silu_f(float x) { return x / (1.0f + __expf(-x)); }
__device__ __forceinline__ float warp_max(float x) {
  int i = __float_as_int(x);
  i ^= (i >> 31) & 0x7fffffff;
  i = __reduce_max_sync(0xffffffffu, i);
  i ^= (i >> 31) & 0x7fffffff;
  return __int_as_float(i);
}
__device__ __forceinline__ void bar_sync(int id, int n) { asm volatile("bar.sync %0, %1;" ::"r"(id), "r"(n) : "memory"); }
__device__ __forceinline__ void bar_arrive(int id, int n) { asm volatile("bar.arrive %0, %1;" ::"r"(id), "r"(n) : "memory"); }
__device__ __forceinline__ void red_release(unsigned* p, unsigned v) {
  asm volatile("red.release.gpu.global.add.u32 [%0], %1;" ::"l"(p), "r"(v) : "memory");
}
__device__ __forceinline__ void red_relaxed(unsigned* p, unsigned v) {
  asm volatile("red.relaxed.gpu.global.add.u32 [%0], %1;" ::"l"(p), "r"(v) : "memory");
}
__device__ __forceinline__ unsigned ld_acquire(const unsigned* p) {
  unsigned v;
  asm volatile("ld.acquire.gpu.global.u32 %0, [%1];" : "=r"(v) : "l"(p) : "memory");
  return v;
}
__device__ __forceinline__ unsigned atom_add(unsigned* p, unsigned v) {
  unsigned r;
  asm volatile("atom.relaxed.gpu.global.add.u32 %0, [%1], %2;" : "=r"(r) : "l"(p), "r"(v) : "memory");
  return r;
}
__device__ __forceinline__ void poll_ge(const unsigned* p, unsigned target, unsigned sleep_ns) {
  int it = 0;
  while (ld_acquire(p) < target) {
    if (sleep_ns) __nanosleep(sleep_ns);
    if (++it > kSpinLimit) KTRAP();
  }
}
__device__ __forceinline__ float4 ldx4(const float* p) {
  float4 v;
  asm volatile("ld.relaxed.gpu.global.v4.f32 {%0,%1,%2,%3}, [%4];" : "=f"(v.x), "=f"(v.y), "=f"(v.z), "=f"(v.w) : "l"(p) : "memory");
  return v;
}
__device__ __forceinline__ float nz(float v) { return __float_as_uint(v) == 0u ? -0.0f : v; }
__device__ __forceinline__ void stx4(float* p, float4 v) {
  asm volatile("st.relaxed.gpu.global.v4.f32 [%0], {%1,%2,%3,%4};" ::"l"(p), "f"(nz(v.x)), "f"(nz(v.y)), "f"(nz(v.z)), "f"(nz(v.w)) : "memory");
}
__device__ __forceinline__ void stx2(float* p, float a, float b) {
  asm volatile("st.relaxed.gpu.global.v2.f32 [%0], {%1,%2};" ::"l"(p), "f"(nz(a)), "f"(nz(b)) : "memory");
}
__device__ __forceinline__ void clr4(float* p) {
  asm volatile("st.relaxed.gpu.global.v4.f32 [%0], {%1,%1,%1,%1};" ::"l"(p), "f"(0.0f) : "memory");
}
__device__ __forceinline__ bool full4(const float4& v) {
  return __float_as_uint(v.x) != 0u && __float_as_uint(v.y) != 0u && __float_as_uint(v.z) != 0u && __float_as_uint(v.w) != 0u;
}
template <int N>
__device__ __forceinline__ void gather(float4 (&v)[N], const float* p, int stride, int cnt, unsigned sleep_ns) {
#pragma unroll
  for (int k = 0; k < N; k++) v[k] = (k < cnt) ? ldx4(p + k * stride) : make_float4(-0.f, -0.f, -0.f, -0.f);
  for (int it = 0;; it++) {
    bool ok = true;
#pragma unroll
    for (int k = 0; k < N; k++) ok = ok && full4(v[k]);
    if (__all_sync(0xffffffffu, ok)) break;
    if (it > kSpinLimit) KTRAP();
    __nanosleep(sleep_ns);
#pragma unroll
    for (int k = 0; k < N; k++)
      if (!full4(v[k])) v[k] = ldx4(p + k * stride);
  }
}

__device__ __forceinline__ void gather18(float4 (&v)[18], const float* po, const float* pml) {
#pragma unroll
  for (int k = 0; k < 18; k++) v[k] = ldx4(k < 16 ? po + k * 1024 : pml + (k - 16) * 128);
  for (int it = 0;; it++) {
    bool ok = true;
#pragma unroll
    for (int k = 0; k < 18; k++) ok = ok && full4(v[k]);
    if (__all_sync(0xffffffffu, ok)) break;
    if (it > kSpinLimit) KTRAP();
    __nanosleep(40);
#pragma unroll
    for (int k = 0; k < 18; k++)
      if (!full4(v[k])) v[k] = ldx4(k < 16 ? po + k * 1024 : pml + (k - 16) * 128);
  }
}

struct Maps {
  CUtensorMap k, v, wq, wo, wg, wu, wd;
};

__global__ void __launch_bounds__(kThreads, 1)
fused_decode_kernel(const __grid_constant__ Maps maps, const __nv_bfloat16* __restrict__ x,
                    __nv_bfloat16* __restrict__ out) {
  extern __shared__ unsigned char smem_dyn[];
  unsigned char* sm = smem_dyn + ((1024u - (smem_u32(smem_dyn) & 1023u)) & 1023u);
  const uint32_t sb = smem_u32(sm);
  const int tid = threadIdx.x, warp = tid >> 5, lane = tid & 31;
  const int cta = blockIdx.x, G = gridDim.x;
  const uint32_t barFull = sb + kOffBar, barEmpty = barFull + kSlots * 8, barInfo = barEmpty + kSlots * 8;
  const uint32_t barMfull = barInfo + kSlots * 8, barMempty = barMfull + 16;
  const uint32_t barWq = barMempty + 16, barWo = barWq + 8, barD = barWo + 8, barQ = barD + 8;
  volatile int* info = reinterpret_cast<volatile int*>(sm + kOffInfo);
  constexpr int kLastBatch = kNAtt - kHKV * kItemsPerPair;

  uint2 xr[9];
  if (warp < 4) {
    const uint2* xp = reinterpret_cast<const uint2*>(x + (warp * 2 + (lane >> 4)) * kD) + (lane & 15);
#pragma unroll
    for (int i = 0; i < 9; i++) xr[i] = __ldg(xp + i * 16);
  }
  if (warp == 5 && lane < 7)
    asm volatile("prefetch.tensormap [%0];" ::"l"(reinterpret_cast<const CUtensorMap*>(&maps) + lane) : "memory");
  unsigned nextDyn = 0;
  if (tid == 128) {
    TS(0);
    nextDyn = atom_add(&g_ctr.claim, 1);
    for (int i = 0; i < 3 * kSlots; i++) mbar_init(barFull + i * 8, 1);
    mbar_init(barMfull, 4); mbar_init(barMfull + 8, 4);
    mbar_init(barMempty, 1); mbar_init(barMempty + 8, 1);
    mbar_init(barWq, 1); mbar_init(barWo, 1); mbar_init(barD, 4); mbar_init(barQ, 4);
    asm volatile("fence.mbarrier_init.release.cluster;" ::: "memory");
  }
  __syncthreads();

  if (warp == 4) {
    if (lane == 0) {
      uint64_t pol;
      asm volatile("createpolicy.fractional.L2::evict_first.b64 %0, 1.0;" : "=l"(pol));
      if (cta < kSliceCtas) {
        mbar_expect_tx(barWq, 36864);
#pragma unroll
        for (int w = 0; w < 4; w++) tma2d(sb + kOffW + w * 9216, &maps.wq, cta * 32, w * 144, barWq, pol);
      }
      TS(19);
      int item = cta, k = 0, n = 0, slot = 0, lslot = 0;
      uint32_t eph = 1, lph = 0;
      while (true) {
        const int nsub = item < kNFfn ? 12 : 4;
#pragma unroll 1
        for (int w = 0; w < nsub; w++, n++) {
          if (n >= KINFL && item < kNItems) {
            if (item >= kNItems - KTAILITEMS && item < kNItems - KLASTFREE) mbar_wait(barFull + lslot * 8, lph);
            if (++lslot == kSlots) { lslot = 0; lph ^= 1; }
          }
          mbar_wait(barEmpty + slot * 8, eph);
          info[slot] = item;
          mbar_arrive(barInfo + slot * 8);
          const uint32_t fb = barFull + slot * 8;
          const uint32_t dst = sb + kOffRing + slot * kSlotBytes;
          if (item >= kNFfn) {
            if (item < kNItems) {
              mbar_expect_tx(fb, kSlotBytes);
              const int row = (item - kNFfn) * kItemRows + w * 32;
              tma3d(dst, &maps.k, 0, row, 0, fb, pol);
              tma3d(dst + 8192, &maps.v, 0, row, 0, fb, pol);
            }
          } else {
            mbar_expect_tx(fb, 9216);
            const int c = (w & 3) * 144;
            if (w < 8) tma2d(dst, w < 4 ? &maps.wg : &maps.wu, item * 32, c, fb, pol);
            else tma2d(dst, &maps.wd, c, item * 32, fb, pol);
          }
          if (++slot == kSlots) { slot = 0; eph ^= 1; }
        }
        if (item >= kNItems) break;
        if (++k < kStaticItems) {
          item = cta + k * G;
        } else {
          item = (int)nextDyn + kStaticItems * G;
          if (item < kNItems) {
            nextDyn = atom_add(&g_ctr.claim, 1);
          } else if (cta < kSliceCtas) {
            mbar_expect_tx(barWo, 36864);
            tma4d(sb + kOffW, &maps.wo, 0, (cta & 7) * 16, (cta >> 3) * 2, 0, barWo, pol);
          }
        }
      }
      TS(3);
    }
  } else if (warp == 5) {
    const float* mb = reinterpret_cast<const float*>(sm + kOffMbuf);
    int pend = -1;
    bool zok = false;
    if (cta < kSliceCtas && lane == 0) {
      mbar_wait(barQ, 0);
      red_release(&g_ctr.qready, 1);
      TS(10);
    }
    __syncwarp();
    for (int kk = 0;; kk++) {
      const int buf = kk & 1;
      mbar_wait(barMfull + buf * 8, (kk >> 1) & 1);
      const float* p = mb + buf * 4 * kMbufStride;
      const int item = __float_as_int(p[260]);
      if (pend >= 0 && lane == 0) red_release(&g_ctr.done[pend * 32], 1);
      if (item < 0) break;
      if (!zok && item >= kLastBatch) {
        if (lane == 0) poll_ge(&g_ctr.zready, kSliceCtas * 2, 100);
        __syncwarp();
        zok = true;
      }
      float4 ml[4];
#pragma unroll
      for (int w = 0; w < 4; w++) ml[w] = *reinterpret_cast<const float4*>(p + w * kMbufStride + 256);
      const float M0 = fmaxf(fmaxf(ml[0].x, ml[1].x), fmaxf(ml[2].x, ml[3].x));
      const float M1 = fmaxf(fmaxf(ml[0].z, ml[1].z), fmaxf(ml[2].z, ml[3].z));
      float4 a = make_float4(0.f, 0.f, 0.f, 0.f), b = a;
      float L0 = 0.f, L1 = 0.f;
#pragma unroll
      for (int w = 0; w < 4; w++) {
        const float s0 = ex2(ml[w].x - M0), s1 = ex2(ml[w].z - M1);
        L0 = fmaf(s0, ml[w].y, L0);
        L1 = fmaf(s1, ml[w].w, L1);
        const float4 u = *reinterpret_cast<const float4*>(p + w * kMbufStride + lane * 4);
        const float4 v = *reinterpret_cast<const float4*>(p + w * kMbufStride + 128 + lane * 4);
        a.x = fmaf(s0, u.x, a.x); a.y = fmaf(s1, u.y, a.y); a.z = fmaf(s0, u.z, a.z); a.w = fmaf(s1, u.w, a.w);
        b.x = fmaf(s0, v.x, b.x); b.y = fmaf(s1, v.y, b.y); b.z = fmaf(s0, v.z, b.z); b.w = fmaf(s1, v.w, b.w);
      }
      float* dst = g_po + (size_t)item * 256;
      stx4(dst + lane * 4, a);
      stx4(dst + 128 + lane * 4, b);
      if (lane < 8)
        stx4(reinterpret_cast<float*>(g_pml + ((item >> 6) * 8 + lane) * kItemsPerPair + (item & 63)), make_float4(M0, L0, M1, L1));
      __syncwarp();
      pend = item >> 6;
      if (lane == 0) {
        mbar_arrive(barMempty + buf * 8);
        if (item >= kLastBatch) red_relaxed(&g_ctr.done[pend * 32], 1);
      }
      if (item >= kLastBatch) pend = -1;
    }
    if (lane == 0) { TS(4); }
  } else if (warp >= 6) {
    const int cw = warp - 6;
    const int ci64 = tid - 192;
    if (lane == 0) poll_ge(&g_ctr.qready, kSliceCtas, 500);
    __syncwarp();
    if (ci64 == 0) {
      mbar_wait(barD, 0);
      red_release(&g_ctr.ddone, 1);
    }
    if (cta < kFinalCtas) {
      if (lane == 0) poll_ge(&g_ctr.ddone, G, 500);
      __syncwarp();
      float* ssum = reinterpret_cast<float*>(sm + kOffSsum);
      if (ci64 < 60) {
        const int q = ci64 % 12, pg = ci64 / 12;
        float4 acc = make_float4(0.f, 0.f, 0.f, 0.f);
#pragma unroll 4
        for (int p = pg; p < G; p += 5) {
          const float4 v = ldx4(g_dp + p * kOutElems + cta * 48 + q * 4);
          acc.x += v.x; acc.y += v.y; acc.z += v.z; acc.w += v.w;
        }
        *reinterpret_cast<float4*>(ssum + pg * 48 + q * 4) = acc;
      }
      bar_sync(2, 64);
      if (ci64 < 48) {
        const float d = (ssum[ci64] + ssum[48 + ci64]) + (ssum[96 + ci64] + ssum[144 + ci64]) + ssum[192 + ci64];
        ssum[240 + ci64] = bf16r(silu_f(bf16r(d)));
      }
      bar_arrive(3, 192);
    }
    if (cta < kSliceCtas) {
      const int kvh = cta >> 3, sl = cta & 7;
      float2* wbuf = reinterpret_cast<float2*>(sm + kOffWbuf) + cw * 64;
      __nv_bfloat16* os = reinterpret_cast<__nv_bfloat16*>(sm + kOffOs);
      const int ci = lane >> 3, q4 = lane & 7;
#pragma unroll 1
      for (int b = cw; b < kB; b += 2) {
        const int pair = b * kHKV + kvh;
        if (b == 4 + cw) {
#pragma unroll 2
          for (int k = 0; k < 18; k++) clr4(g_sp + cta * kOutElems + (k * 64 + ci64) * 4);
          const int pair7 = 7 * kHKV + kvh;
#pragma unroll 2
          for (int k = 0; k < 8; k++)
            clr4(g_po + ((size_t)pair7 * kItemsPerPair + k * 8 + (ci64 >> 3)) * 256 + sl * 32 + (ci64 & 7) * 4);
          clr4(reinterpret_cast<float*>(g_pml + (pair7 * 8 + sl) * kItemsPerPair + ci64));
          __syncwarp();
          if (lane == 0) red_release(&g_ctr.zready, 1);
        }
        if (b == 7 && lane == 0) poll_ge(&g_ctr.zready, kSliceCtas * 2, 100);
        const float* pml = reinterpret_cast<const float*>(g_pml + (pair * 8 + sl) * kItemsPerPair);
        if (lane == 0) poll_ge(&g_ctr.done[pair * 32], b == 7 ? KGATE7 : kItemsPerPair, b == 7 ? 60 : 300);
        __syncwarp();
        const float* po = g_po + (size_t)pair * kItemsPerPair * 256 + sl * 32 + q4 * 4 + ci * 256;
        float4 v[18];
        if (b == 7 && lane == 0) { TS(27); }
        gather18(v, po, pml + lane * 4);
        __syncwarp();
        if (b == 7 && lane == 0) { TS(28); }
        const float4 mlA = v[16], mlB = v[17];
        const float M0 = warp_max(fmaxf(mlA.x, mlB.x)), M1 = warp_max(fmaxf(mlA.z, mlB.z));
        const float wA0 = ex2(mlA.x - M0), wA1 = ex2(mlA.z - M1), wB0 = ex2(mlB.x - M0), wB1 = ex2(mlB.z - M1);
        float L0 = wA0 * mlA.y + wB0 * mlB.y, L1 = wA1 * mlA.w + wB1 * mlB.w;
        wbuf[lane] = make_float2(wA0, wA1);
        wbuf[32 + lane] = make_float2(wB0, wB1);
        __syncwarp();
        float4 acc = make_float4(0.f, 0.f, 0.f, 0.f);
#pragma unroll
        for (int k = 0; k < 16; k++) {
          const float2 w2 = wbuf[k * 4 + ci];
          acc.x = fmaf(w2.x, v[k].x, acc.x); acc.y = fmaf(w2.y, v[k].y, acc.y);
          acc.z = fmaf(w2.x, v[k].z, acc.z); acc.w = fmaf(w2.y, v[k].w, acc.w);
        }
#pragma unroll
        for (int o = 1; o <= 16; o <<= 1) {
          L0 += __shfl_xor_sync(0xffffffffu, L0, o);
          L1 += __shfl_xor_sync(0xffffffffu, L1, o);
          if (o >= 8) {
            acc.x += __shfl_xor_sync(0xffffffffu, acc.x, o); acc.y += __shfl_xor_sync(0xffffffffu, acc.y, o);
            acc.z += __shfl_xor_sync(0xffffffffu, acc.z, o); acc.w += __shfl_xor_sync(0xffffffffu, acc.w, o);
          }
        }
        if (lane < 8) {
          const float r0 = 1.0f / L0, r1 = 1.0f / L1;
          *reinterpret_cast<uint32_t*>(os + b * 40 + q4 * 2) = pack_bf16(acc.x * r0, acc.z * r0);
          *reinterpret_cast<uint32_t*>(os + b * 40 + 16 + q4 * 2) = pack_bf16(acc.y * r1, acc.w * r1);
        }
        __syncwarp();
      }
      if (lane == 0) { TS(5 + cw); }
      bar_arrive(4, 192);
    }
  } else {
    const int g = lane >> 2, t = lane & 3;
    __nv_bfloat16* xn = reinterpret_cast<__nv_bfloat16*>(sm + kOffXn);
    {
      float v[36];
#pragma unroll
      for (int i = 0; i < 9; i++) {
        v[4 * i] = __uint_as_float(xr[i].x << 16);
        v[4 * i + 1] = __uint_as_float(xr[i].x & 0xffff0000u);
        v[4 * i + 2] = __uint_as_float(xr[i].y << 16);
        v[4 * i + 3] = __uint_as_float(xr[i].y & 0xffff0000u);
      }
      float s = 0.f;
#pragma unroll
      for (int i = 0; i < 36; i++) s += v[i];
#pragma unroll
      for (int o = 8; o > 0; o >>= 1) s += __shfl_xor_sync(0xffffffffu, s, o);
      const float mean = s * (1.0f / kD);
      float q = 0.f;
#pragma unroll
      for (int i = 0; i < 36; i++) { const float d = v[i] - mean; q = fmaf(d, d, q); }
#pragma unroll
      for (int o = 8; o > 0; o >>= 1) q += __shfl_xor_sync(0xffffffffu, q, o);
      const float mb = bf16r(mean);
      const float rden = 1.0f / bf16r(sqrtf(bf16r(bf16r(q * (1.0f / kD)) + 1e-5f)));
      __nv_bfloat16* xw = xn + (warp * 2 + (lane >> 4)) * kXnPitch + (lane & 15) * 4;
#pragma unroll
      for (int i = 0; i < 9; i++)
        *reinterpret_cast<uint2*>(xw + i * 64) =
            make_uint2(pack_bf16(bf16r(v[4 * i] - mb) * rden, bf16r(v[4 * i + 1] - mb) * rden),
                       pack_bf16(bf16r(v[4 * i + 2] - mb) * rden, bf16r(v[4 * i + 3] - mb) * rden));
    }
    bar_sync(1, 128);
    if (tid == 0) { TS(18); }
    float* mb = reinterpret_cast<float*>(sm + kOffMbuf);
    const uint32_t r8 = lane & 7;
    const uint32_t guLane = (r8 + (lane >> 4) * 8) * 64 + ((((lane >> 3) & 1) ^ (r8 >> 1)) << 4);
    int slot = warp, item;
    uint32_t fph = 0;
    {
      uint32_t xb[9][2];
#pragma unroll
      for (int ks = 0; ks < 9; ks++) {
        xb[ks][0] = *reinterpret_cast<const uint32_t*>(xn + g * kXnPitch + warp * 144 + ks * 16 + t * 2);
        xb[ks][1] = *reinterpret_cast<const uint32_t*>(xn + g * kXnPitch + warp * 144 + ks * 16 + 8 + t * 2);
      }
      if (cta < kSliceCtas) {
        if (tid == 0) {
          g_ctr.done[cta * 32] = 0;
          if (cta == 0) { g_ctr.ddone = 0; g_ctr.zready = 0; g_ctr.exitc = 0; }
        }
        mbar_wait(barWq, 0);
        if (tid == 0) { TS(9); }
        const uint32_t lo = sb + kOffW + warp * 9216;
        uint32_t a[18][4];
#pragma unroll
        for (int i = 0; i < 18; i++) ldsm4t(a[i], lo + (guLane ^ ((i & 1) * 32)) + (i >> 1) * 1024);
        float c[2][4] = {{0.f, 0.f, 0.f, 0.f}, {0.f, 0.f, 0.f, 0.f}};
#pragma unroll
        for (int i = 0; i < 18; i++) mma16816(c[i & 1], a[i], xb[i >> 1][0], xb[i >> 1][1]);
        float* qr = mb + warp * 256;
#pragma unroll
        for (int mt = 0; mt < 2; mt++) {
          *reinterpret_cast<float2*>(qr + (mt * 16 + g) * 8 + t * 2) = make_float2(c[mt][0], c[mt][1]);
          *reinterpret_cast<float2*>(qr + (mt * 16 + 8 + g) * 8 + t * 2) = make_float2(c[mt][2], c[mt][3]);
        }
        bar_sync(1, 128);
        const int b = tid >> 4, cp = tid & 15;
        float q0 = 0.f, q1 = 0.f;
#pragma unroll
        for (int w = 0; w < 4; w++) {
          q0 += mb[w * 256 + (cp * 2) * 8 + b];
          q1 += mb[w * 256 + (cp * 2 + 1) * 8 + b];
        }
        const int col = cta * 32 + cp * 2;
        const int head = col >> 7, d = col & 127;
        const int pos = (head & 1) * 128 + (d >> 5) * 32 + ((d & 7) >> 1) * 8 + ((d >> 4) & 1) * 4 + ((d >> 3) & 1) * 2;
        *reinterpret_cast<uint32_t*>(g_q + (b * kHKV + (head >> 1)) * 256 + pos) = pack_bf16(q0, q1);
        __syncwarp();
        if (lane == 0) mbar_arrive(barQ);
        if (tid == 32) { TS(17); }
      } else {
        bar_sync(1, 128);
      }

      float dacc[9][4];
#pragma unroll
      for (int i = 0; i < 9; i++) dacc[i][0] = dacc[i][1] = dacc[i][2] = dacc[i][3] = 0.f;
      float* red = reinterpret_cast<float*>(sm + kOffXn);
      const uint32_t dnLane = (r8 + (lane >> 4) * 8) * 288 + ((lane >> 3) & 1) * 16;
      while (true) {
        mbar_wait(barInfo + slot * 8, fph);
        item = info[slot];
        if (item >= kNFfn) break;
        uint32_t a[18][4];
        float* rw = red + warp * 512;
#pragma unroll 1
        for (int gu = 0; gu < 2; gu++) {
          mbar_wait(barFull + slot * 8, fph);
          const uint32_t base = sb + kOffRing + slot * kSlotBytes;
#pragma unroll
          for (int i = 0; i < 18; i++) ldsm4t(a[i], base + (guLane ^ ((i & 1) * 32)) + (i >> 1) * 1024);
          float c[2][4] = {{0.f, 0.f, 0.f, 0.f}, {0.f, 0.f, 0.f, 0.f}};
#pragma unroll
          for (int i = 0; i < 18; i++) mma16816(c[i & 1], a[i], xb[i >> 1][0], xb[i >> 1][1]);
#pragma unroll
          for (int mt = 0; mt < 2; mt++) {
            float* r = rw + gu * 256 + (2 * t) * 32 + mt * 16 + g;
            r[0] = c[mt][0]; r[32] = c[mt][1]; r[8] = c[mt][2]; r[40] = c[mt][3];
          }
          __syncwarp();
          if (lane == 0) mbar_arrive(barEmpty + slot * 8);
          slot += 4;
          if (slot >= kSlots) { slot -= kSlots; fph ^= 1; }
        }
        bar_sync(1, 128);
        uint32_t hb[4];
#pragma unroll
        for (int j = 0; j < 4; j++) {
          float2 gs = make_float2(0.f, 0.f), us = gs;
#pragma unroll
          for (int w = 0; w < 4; w++) {
            const float* rr = red + w * 512 + g * 32 + j * 8 + t * 2;
            const float2 a2 = *reinterpret_cast<const float2*>(rr), b2 = *reinterpret_cast<const float2*>(rr + 256);
            gs.x += a2.x; gs.y += a2.y; us.x += b2.x; us.y += b2.y;
          }
          hb[j] = pack_bf16(bf16r(silu_f(bf16r(gs.x))) * bf16r(us.x), bf16r(silu_f(bf16r(gs.y))) * bf16r(us.y));
        }
        mbar_wait(barFull + slot * 8, fph);
        const uint32_t base = sb + kOffRing + slot * kSlotBytes + dnLane;
#pragma unroll
        for (int i = 0; i < 18; i++) ldsm4t(a[i], base + (i >> 1) * 32 + (i & 1) * 4608);
#pragma unroll
        for (int i = 0; i < 18; i++) mma16816(dacc[i >> 1], a[i], hb[(i & 1) * 2], hb[(i & 1) * 2 + 1]);
        bar_sync(1, 128);
        if (lane == 0) mbar_arrive(barEmpty + slot * 8);
        slot += 4;
        if (slot >= kSlots) { slot -= kSlots; fph ^= 1; }
      }
      if (tid == 0) { TS(12); }
      float* dp = g_dp + cta * kOutElems + (warp * 144 + g) * 8 + t * 2;
#pragma unroll
      for (int mt = 0; mt < 9; mt++) {
        *reinterpret_cast<float2*>(dp + mt * 128) = make_float2(dacc[mt][0], dacc[mt][1]);
        *reinterpret_cast<float2*>(dp + mt * 128 + 64) = make_float2(dacc[mt][2], dacc[mt][3]);
      }
      __syncwarp();
      if (lane == 0) {
        mbar_arrive(barD);
        poll_ge(&g_ctr.qready, kSliceCtas, 20);
      }
      __syncwarp();
      if (tid == 0) { TS(2); }
    }

    const float kScale = 0.08838834764831845f * 1.4426950408889634f;
    const uint32_t kLane = (r8 + ((lane >> 3) & 1) * 8) * 128 + (((lane >> 4) ^ r8) << 4);
    const uint32_t vLane = 8192 + (r8 + (lane >> 4) * 8) * 128 + ((((lane >> 3) & 1) ^ r8) << 4);
    int kk = 0;
    while (item < kNItems) {
      item -= kNFfn;
      uint4 qv[4];
      if (g < 2) {
        const uint4* qs = reinterpret_cast<const uint4*>(g_q + (item >> 6) * 256 + g * 128 + t * 8);
#pragma unroll
        for (int i = 0; i < 4; i++) qv[i] = qs[i * 4];
      } else {
#pragma unroll
        for (int i = 0; i < 4; i++) qv[i] = make_uint4(0u, 0u, 0u, 0u);
      }
      mbar_wait(barFull + slot * 8, fph);
      const uint32_t base = sb + kOffRing + slot * kSlotBytes;
      uint32_t ka[16][4], va[16][4];
#pragma unroll
      for (int i = 0; i < 16; i++)
        ldsm4(ka[i], base + ((kLane ^ (((i >> 1) & 3) << 5)) + (i >> 3) * 4096 + (i & 1) * 2048));
#pragma unroll
      for (int i = 0; i < 16; i++)
        ldsm4t(va[i], base + ((vLane ^ (((i >> 1) & 3) << 5)) + (i >> 3) * 4096 + (i & 1) * 2048));
      float s[2][4], s2[2][4];
#pragma unroll
      for (int i = 0; i < 4; i++) s[0][i] = s[1][i] = s2[0][i] = s2[1][i] = 0.f;
#pragma unroll
      for (int kp = 0; kp < 4; kp++) {
        mma16816(s[0], ka[4 * kp], qv[kp].x, qv[kp].y);
        mma16816(s[1], ka[4 * kp + 1], qv[kp].x, qv[kp].y);
        mma16816(s2[0], ka[4 * kp + 2], qv[kp].z, qv[kp].w);
        mma16816(s2[1], ka[4 * kp + 3], qv[kp].z, qv[kp].w);
      }
#pragma unroll
      for (int i = 0; i < 4; i++) { s[0][i] += s2[0][i]; s[1][i] += s2[1][i]; }
      float m0 = fmaxf(fmaxf(s[0][0], s[0][2]), fmaxf(s[1][0], s[1][2]));
      float m1 = fmaxf(fmaxf(s[0][1], s[0][3]), fmaxf(s[1][1], s[1][3]));
#pragma unroll
      for (int o = 4; o <= 16; o <<= 1) {
        m0 = fmaxf(m0, __shfl_xor_sync(0xffffffffu, m0, o));
        m1 = fmaxf(m1, __shfl_xor_sync(0xffffffffu, m1, o));
      }
      m0 *= kScale; m1 *= kScale;
      float l0 = 0.f, l1 = 0.f;
      uint32_t pb[2][2];
#pragma unroll
      for (int mt = 0; mt < 2; mt++) {
        const float p0 = ex2(fmaf(s[mt][0], kScale, -m0)), p1 = ex2(fmaf(s[mt][1], kScale, -m1));
        const float p2 = ex2(fmaf(s[mt][2], kScale, -m0)), p3 = ex2(fmaf(s[mt][3], kScale, -m1));
        l0 += p0 + p2; l1 += p1 + p3;
        pb[mt][0] = movmat(pack_bf16(p0, p1));
        pb[mt][1] = movmat(pack_bf16(p2, p3));
      }
      float o_[8][4];
#pragma unroll
      for (int j = 0; j < 8; j++) {
        o_[j][0] = o_[j][1] = o_[j][2] = o_[j][3] = 0.f;
        mma16816(o_[j], va[2 * j], pb[0][0], pb[0][1]);
      }
#pragma unroll
      for (int j = 0; j < 8; j++) mma16816(o_[j], va[2 * j + 1], pb[1][0], pb[1][1]);
#pragma unroll
      for (int o = 4; o <= 16; o <<= 1) {
        l0 += __shfl_xor_sync(0xffffffffu, l0, o);
        l1 += __shfl_xor_sync(0xffffffffu, l1, o);
      }
      const int buf = kk & 1;
      mbar_wait(barMempty + buf * 8, ((kk >> 1) & 1) ^ 1);
      float* p = mb + (buf * 4 + warp) * kMbufStride;
      if (t == 0) {
#pragma unroll
        for (int j = 0; j < 8; j++) {
          *reinterpret_cast<float2*>(p + (j * 16 + g) * 2) = make_float2(o_[j][0], o_[j][1]);
          *reinterpret_cast<float2*>(p + (j * 16 + 8 + g) * 2) = make_float2(o_[j][2], o_[j][3]);
        }
        if (g == 0) {
          *reinterpret_cast<float4*>(p + 256) = make_float4(m0, l0, m1, l1);
          p[260] = __int_as_float(item);
        }
      }
      __syncwarp();
      if (lane == 0) {
        mbar_arrive(barMfull + buf * 8);
        mbar_arrive(barEmpty + slot * 8);
      }
      kk++;
      slot += 4;
      if (slot >= kSlots) { slot -= kSlots; fph ^= 1; }
      mbar_wait(barInfo + slot * 8, fph);
      item = info[slot];
    }
    {
      const int buf = kk & 1;
      mbar_wait(barMempty + buf * 8, ((kk >> 1) & 1) ^ 1);
      if (lane == 0) {
        mb[(buf * 4 + warp) * kMbufStride + 260] = __int_as_float(-1);
        mbar_arrive(barMfull + buf * 8);
        poll_ge(&g_ctr.zready, kSliceCtas * 2, 100);
        if (warp == 0) red_relaxed(&g_ctr.exitc, 1);
      }
      __syncwarp();
    }
    if (tid == 0) { TS(11); }
    float xv = 0.f;
    if (cta < kFinalCtas && tid < 48) xv = __bfloat162float(x[(tid & 7) * kD + cta * 6 + (tid >> 3)]);
    if (cta < kSliceCtas) {
      mbar_wait(barWo, 0);
      if (tid == 0) { TS(29); }
      const uint32_t wl = (r8 + (lane >> 4) * 8) * 128 + ((((lane >> 3) & 1) ^ r8) << 4);
      uint32_t a[18][4];
#pragma unroll
      for (int mt = 0; mt < 9; mt++) {
        const int tile = warp * 9 + mt;
        const uint32_t ad = sb + kOffW + (tile >> 2) * 4096 + (wl ^ ((tile & 3) << 5));
        ldsm4t(a[2 * mt], ad);
        ldsm4t(a[2 * mt + 1], ad + 2048);
      }
      bar_sync(4, 192);
      const __nv_bfloat16* os = reinterpret_cast<const __nv_bfloat16*>(sm + kOffOs) + g * 40 + t * 2;
      const uint32_t ob0 = *reinterpret_cast<const uint32_t*>(os), ob1 = *reinterpret_cast<const uint32_t*>(os + 8);
      const uint32_t ob2 = *reinterpret_cast<const uint32_t*>(os + 16), ob3 = *reinterpret_cast<const uint32_t*>(os + 24);
      float* sp = g_sp + cta * kOutElems + (warp * 144 + g) * 8 + t * 2;
#pragma unroll
      for (int mt = 0; mt < 9; mt++) {
        float c[4] = {0.f, 0.f, 0.f, 0.f};
        mma16816(c, a[2 * mt], ob0, ob1);
        mma16816(c, a[2 * mt + 1], ob2, ob3);
        stx2(sp + mt * 128, c[0], c[1]);
        stx2(sp + mt * 128 + 64, c[2], c[3]);
      }
      if (tid == 0) { TS(7); TS(8); }
    }
    if (cta < kFinalCtas) {
      float* fsum = reinterpret_cast<float*>(sm + kOffFsum);
      {
        const int q = tid % 12, pg = tid / 12;
        float4 v[13];
        gather<13>(v, g_sp + cta * 48 + q * 4 + pg * kOutElems, 10 * kOutElems, pg < 8 ? 13 : (pg < 10 ? 12 : 0), 20);
        float4 acc = v[0];
#pragma unroll
        for (int k = 1; k < 13; k++) { acc.x += v[k].x; acc.y += v[k].y; acc.z += v[k].z; acc.w += v[k].w; }
        if (tid < 120) *reinterpret_cast<float4*>(fsum + pg * 48 + q * 4) = acc;
      }
      if (tid == 0) { TS(13); }
      bar_sync(3, 192);
      if (tid < 48) {
        float s = 0.f;
#pragma unroll
        for (int k = 0; k < 10; k++) s += fsum[k * 48 + tid];
        const float gt = reinterpret_cast<const float*>(sm + kOffSsum)[240 + tid];
        out[(tid & 7) * kD + cta * 6 + (tid >> 3)] = __float2bfloat16_rn(xv + bf16r(bf16r(s) * gt));
      }
      if (cta == 0 && tid == 64) {
        poll_ge(&g_ctr.exitc, G, 20);
        g_ctr.claim = 0;
        g_ctr.qready = 0;
      }
    }
    if (tid == 0) { TS(14); }
  }
}

typedef CUresult (*EncodeFn)(CUtensorMap*, CUtensorMapDataType, cuuint32_t, void*, const cuuint64_t*,
                             const cuuint64_t*, const cuuint32_t*, const cuuint32_t*, CUtensorMapInterleave,
                             CUtensorMapSwizzle, CUtensorMapL2promotion, CUtensorMapFloatOOBfill);

void encode(EncodeFn fn, CUtensorMap* m, const void* base, int rank, const cuuint64_t* dims, const cuuint64_t* strides,
            const cuuint32_t* box, CUtensorMapSwizzle sw) {
  const cuuint32_t es[4] = {1, 1, 1, 1};
  fn(m, CU_TENSOR_MAP_DATA_TYPE_BFLOAT16, rank, const_cast<void*>(base), dims, strides, box, es,
     CU_TENSOR_MAP_INTERLEAVE_NONE, sw, CU_TENSOR_MAP_L2_PROMOTION_L2_256B, CU_TENSOR_MAP_FLOAT_OOB_FILL_NONE);
}

}

extern "C" void kernel_launch(void* const* d_in, const int* in_sizes, int n_in, void* d_out, int out_size) {
  (void)in_sizes; (void)n_in; (void)out_size;
  static EncodeFn fn = nullptr;
  static int sms = 0;
  if (!fn) {
    void* p = nullptr;
    cudaDriverEntryPointQueryResult qr;
    cudaGetDriverEntryPoint("cuTensorMapEncodeTiled", &p, cudaEnableDefault, &qr);
    fn = (EncodeFn)p;
    int dev = 0;
    cudaGetDevice(&dev);
    cudaDeviceGetAttribute(&sms, cudaDevAttrMultiProcessorCount, dev);
    cudaFuncSetAttribute(fused_decode_kernel, cudaFuncAttributeMaxDynamicSharedMemorySize, kSmemBytes);
  }
  Maps maps;
  {
    const cuuint64_t dims[3] = {64, (cuuint64_t)kPairs * kSK, 2}, str[2] = {256, 128};
    const cuuint32_t box[3] = {64, 32, 2};
    encode(fn, &maps.k, d_in[1], 3, dims, str, box, CU_TENSOR_MAP_SWIZZLE_128B);
    encode(fn, &maps.v, d_in[2], 3, dims, str, box, CU_TENSOR_MAP_SWIZZLE_128B);
  }
  {
    const cuuint64_t dims[2] = {4096, kD}, str[1] = {8192};
    const cuuint32_t box[2] = {32, 144};
    encode(fn, &maps.wq, d_in[3], 2, dims, str, box, CU_TENSOR_MAP_SWIZZLE_64B);
  }
  {
    const cuuint64_t dims[4] = {64, 128, 32, 9}, str[3] = {kD * 2, 128 * kD * 2, 128};
    const cuuint32_t box[4] = {64, 16, 2, 9};
    encode(fn, &maps.wo, d_in[4], 4, dims, str, box, CU_TENSOR_MAP_SWIZZLE_128B);
  }
  {
    const cuuint64_t dims[2] = {kF, kD}, str[1] = {kF * 2};
    const cuuint32_t box[2] = {32, 144};
    encode(fn, &maps.wg, d_in[6], 2, dims, str, box, CU_TENSOR_MAP_SWIZZLE_64B);
    encode(fn, &maps.wu, d_in[7], 2, dims, str, box, CU_TENSOR_MAP_SWIZZLE_64B);
  }
  {
    const cuuint64_t dims[2] = {kD, kF}, str[1] = {kD * 2};
    const cuuint32_t box[2] = {144, 32};
    encode(fn, &maps.wd, d_in[8], 2, dims, str, box, CU_TENSOR_MAP_SWIZZLE_NONE);
  }
  int grid = sms < kMaxCtas ? sms : kMaxCtas;
  fused_decode_kernel<<<grid, kThreads, kSmemBytes>>>(maps, (const __nv_bfloat16*)d_in[0], (__nv_bfloat16*)d_out);
}
```

```cpp
#include <cuda_runtime.h>
#include <cuda_bf16.h>
#include <cuda.h>
#include <stdint.h>

namespace {

constexpr int kB = 8, kD = 576, kHKV = 16, kSK = 8192, kF = 4608;
constexpr int kPairs = kB * kHKV;
constexpr int kItemRows = 128;
constexpr int kItemsPerPair = kSK / kItemRows;
constexpr int kNAtt = kPairs * kItemsPerPair;
constexpr int kNFfn = kF / 32;
constexpr int kNItems = kNAtt + kNFfn;
#define KSLOTS 8
#define KINFL 3
#define KTAILITEMS 0
#define KFIRST 8
#define KTMAST 0
#define KAUXSLEEP 40
#define KWOFIRST 0
#define KLPF 0
#define KDEFER 1
#define KILV 1
#define KCLAIMAT 0
#define KPROMOKV 3
#define KPROMOW 2
#define KPOL "evict_first"
#define KPROMOO 2
#define KPROMOD 2
#define KWPF 1
#define KWOLAND 5
#define KINFLF 8
#define KHEADITEMS 0
constexpr int kMaxCtasCheck = 144;
constexpr int kSlots = KSLOTS;
static_assert(kMaxCtasCheck <= 144, "the first item of every CTA is an FFN unit");
static_assert(kSlots == 8, "a slot must always be consumed by the same warp (mbarrier phase safety)");
constexpr int kSlotBytes = 16384;
constexpr int kStaticItems = 1;
constexpr int kMaxCtas = kMaxCtasCheck;
constexpr int kSliceCtas = 128;
constexpr int kRow7Ctas = 72;
constexpr int kThreads = 256;
constexpr int kOutElems = kB * kD;

constexpr int kOffRing = 0;
constexpr int kOffW = kOffRing + kSlots * kSlotBytes;
constexpr int kOffXn = kOffW + 36864;
constexpr int kXnPitch = 584;
constexpr int kOffMbuf = kOffXn + kB * kXnPitch * 2;
constexpr int kMbufStride = 264;
constexpr int kOffOs = kOffMbuf + 2 * 4 * kMbufStride * 4;
constexpr int kOffWbuf = kOffOs + 8 * 40 * 2;
constexpr int kOffFsum = kOffWbuf + 2 * 64 * 8;
constexpr int kOffSsum = kOffFsum + 14 * 36 * 4;
constexpr int kOffG7 = kOffSsum + 8 * 36 * 4;
constexpr int kOffCbuf = kOffG7 + 104 * 4;
constexpr int kOffInfo = kOffCbuf + 4 * 40 * 4;
constexpr int kOffBar = kOffInfo + 64;
constexpr int kNumBars = 3 * kSlots + 9 + 6;
constexpr int kSmemBytes = kOffBar + kNumBars * 8 + 1024;
static_assert(kSmemBytes <= 232448, "smem");

constexpr int kPartSlots = 48;
__device__ __forceinline__ int PSLOT(int pair) { return pair >= 112 ? pair - 80 : (pair & 31); }

struct Counters {
  unsigned claim;
  unsigned qready; unsigned pad1[30];
  unsigned ddone;  unsigned pad2[31];
  unsigned zready; unsigned pad3[31];
  unsigned exitc;  unsigned pad4[31];
  unsigned cons[8 * 32];
  unsigned done[kPairs * 32];
};

__device__ Counters g_ctr;
__device__ __align__(128) __nv_bfloat16 g_q[kPairs * 256];
__device__ __align__(128) float g_po[kPartSlots * kItemsPerPair * 256];
__device__ __align__(128) float4 g_pml[kPartSlots * 8 * kItemsPerPair];
__device__ __align__(128) float g_sp[kSliceCtas * kOutElems];
__device__ __align__(128) float g_s7[kRow7Ctas * kSliceCtas * 8];
__device__ __align__(128) float g_dp[kMaxCtas * kOutElems];
#define TS(i)

#define KTRAP() __trap()
constexpr int kSpinLimit = 1 << 21;

__device__ __forceinline__ uint32_t smem_u32(const void* p) { return (uint32_t)__cvta_generic_to_shared(p); }
__device__ __forceinline__ void mbar_init(uint32_t bar, uint32_t cnt) {
  asm volatile("mbarrier.init.shared::cta.b64 [%0], %1;" ::"r"(bar), "r"(cnt) : "memory");
}
__device__ __forceinline__ void mbar_expect_tx(uint32_t bar, uint32_t bytes) {
  asm volatile("mbarrier.arrive.expect_tx.shared::cta.b64 _, [%0], %1;" ::"r"(bar), "r"(bytes) : "memory");
}
__device__ __forceinline__ void mbar_arrive(uint32_t bar) {
  asm volatile("mbarrier.arrive.shared::cta.b64 _, [%0];" ::"r"(bar) : "memory");
}
__device__ __forceinline__ void mbar_wait(uint32_t bar, uint32_t parity) {
  uint32_t done;
  int it = 0;
  do {
    asm volatile(
        "{\n.reg .pred p;\nmbarrier.try_wait.parity.shared::cta.b64 p, [%1], %2;\nselp.u32 %0, 1, 0, p;\n}"
        : "=r"(done) : "r"(bar), "r"(parity) : "memory");
    if (++it > kSpinLimit) KTRAP();
  } while (!done);
}
__device__ __forceinline__ bool mbar_test(uint32_t bar, uint32_t parity) {
  uint32_t done;
  asm volatile(
      "{\n.reg .pred p;\nmbarrier.test_wait.parity.shared::cta.b64 p, [%1], %2;\nselp.u32 %0, 1, 0, p;\n}"
      : "=r"(done) : "r"(bar), "r"(parity) : "memory");
  return done != 0;
}
__device__ __forceinline__ void tma2d(uint32_t dst, const CUtensorMap* m, int c0, int c1, uint32_t bar, uint64_t pol) {
  asm volatile(
      "cp.async.bulk.tensor.2d.shared::cluster.global.mbarrier::complete_tx::bytes.L2::cache_hint [%0], [%1, {%3, %4}], [%2], %5;"
      ::"r"(dst), "l"(m), "r"(bar), "r"(c0), "r"(c1), "l"(pol) : "memory");
}
__device__ __forceinline__ void tma3d(uint32_t dst, const CUtensorMap* m, int c0, int c1, int c2, uint32_t bar, uint64_t pol) {
  asm volatile(
      "cp.async.bulk.tensor.3d.shared::cluster.global.mbarrier::complete_tx::bytes.L2::cache_hint [%0], [%1, {%3, %4, %5}], [%2], %6;"
      ::"r"(dst), "l"(m), "r"(bar), "r"(c0), "r"(c1), "r"(c2), "l"(pol) : "memory");
}
__device__ __forceinline__ void tma4d(uint32_t dst, const CUtensorMap* m, int c0, int c1, int c2, int c3, uint32_t bar, uint64_t pol) {
  asm volatile(
      "cp.async.bulk.tensor.4d.shared::cluster.global.mbarrier::complete_tx::bytes.L2::cache_hint [%0], [%1, {%3, %4, %5, %6}], [%2], %7;"
      ::"r"(dst), "l"(m), "r"(bar), "r"(c0), "r"(c1), "r"(c2), "r"(c3), "l"(pol) : "memory");
}
__device__ __forceinline__ void ldsm4(uint32_t (&r)[4], uint32_t addr) {
  asm volatile("ldmatrix.sync.aligned.m8n8.x4.shared.b16 {%0,%1,%2,%3}, [%4];"
               : "=r"(r[0]), "=r"(r[1]), "=r"(r[2]), "=r"(r[3]) : "r"(addr) : "memory");
}
__device__ __forceinline__ void ldsm4t(uint32_t (&r)[4], uint32_t addr) {
  asm volatile("ldmatrix.sync.aligned.m8n8.x4.trans.shared.b16 {%0,%1,%2,%3}, [%4];"
               : "=r"(r[0]), "=r"(r[1]), "=r"(r[2]), "=r"(r[3]) : "r"(addr) : "memory");
}
__device__ __forceinline__ void mma16816(float (&c)[4], const uint32_t (&a)[4], uint32_t b0, uint32_t b1) {
  asm(
      "mma.sync.aligned.m16n8k16.row.col.f32.bf16.bf16.f32 {%0,%1,%2,%3}, {%4,%5,%6,%7}, {%8,%9}, {%0,%1,%2,%3};"
      : "+f"(c[0]), "+f"(c[1]), "+f"(c[2]), "+f"(c[3])
      : "r"(a[0]), "r"(a[1]), "r"(a[2]), "r"(a[3]), "r"(b0), "r"(b1));
}
__device__ __forceinline__ uint32_t movmat(uint32_t a) {
  uint32_t d;
  asm volatile("movmatrix.sync.aligned.m8n8.trans.b16 %0, %1;" : "=r"(d) : "r"(a));
  return d;
}
__device__ __forceinline__ float ex2(float x) {
  float y;
  asm("ex2.approx.ftz.f32 %0, %1;" : "=f"(y) : "f"(x));
  return y;
}
__device__ __forceinline__ uint32_t pack_bf16(float lo, float hi) {
  uint32_t r;
  asm("cvt.rn.bf16x2.f32 %0, %1, %2;" : "=r"(r) : "f"(hi), "f"(lo));
  return r;
}
__device__ __forceinline__ float bf16r(float x) { return __bfloat162float(__float2bfloat16_rn(x)); }
__device__ __forceinline__ float silu_f(float x) { return x / (1.0f + __expf(-x)); }
__device__ __forceinline__ float warp_max(float x) {
  int i = __float_as_int(x);
  i ^= (i >> 31) & 0x7fffffff;
  i = __reduce_max_sync(0xffffffffu, i);
  i ^= (i >> 31) & 0x7fffffff;
  return __int_as_float(i);
}
__device__ __forceinline__ void bar_sync(int id, int n) { asm volatile("bar.sync %0, %1;" ::"r"(id), "r"(n) : "memory"); }
__device__ __forceinline__ void bar_arrive(int id, int n) { asm volatile("bar.arrive %0, %1;" ::"r"(id), "r"(n) : "memory"); }
__device__ __forceinline__ void red_release(unsigned* p, unsigned v) {
  asm volatile("red.release.gpu.global.add.u32 [%0], %1;" ::"l"(p), "r"(v) : "memory");
}
__device__ __forceinline__ void red_relaxed(unsigned* p, unsigned v) {
  asm volatile("red.relaxed.gpu.global.add.u32 [%0], %1;" ::"l"(p), "r"(v) : "memory");
}
__device__ __forceinline__ unsigned ld_acquire(const unsigned* p) {
  unsigned v;
  asm volatile("ld.acquire.gpu.global.u32 %0, [%1];" : "=r"(v) : "l"(p) : "memory");
  return v;
}
__device__ __forceinline__ unsigned ld_relaxed(const unsigned* p) {
  unsigned v;
  asm volatile("ld.relaxed.gpu.global.u32 %0, [%1];" : "=r"(v) : "l"(p) : "memory");
  return v;
}
__device__ __forceinline__ unsigned atom_add(unsigned* p, unsigned v) {
  unsigned r;
  asm volatile("atom.relaxed.gpu.global.add.u32 %0, [%1], %2;" : "=r"(r) : "l"(p), "r"(v) : "memory");
  return r;
}
__device__ __forceinline__ void poll_ge(const unsigned* p, unsigned target, unsigned sleep_ns) {
  int it = 0;
  while (ld_acquire(p) < target) {
    if (sleep_ns) __nanosleep(sleep_ns);
    if (++it > kSpinLimit) KTRAP();
  }
}
__device__ __forceinline__ float4 ldx4(const float* p) {
  float4 v;
  asm volatile("ld.relaxed.gpu.global.v4.f32 {%0,%1,%2,%3}, [%4];" : "=f"(v.x), "=f"(v.y), "=f"(v.z), "=f"(v.w) : "l"(p) : "memory");
  return v;
}
__device__ __forceinline__ float nz(float v) { return __float_as_uint(v) == 0u ? -0.0f : v; }
__device__ __forceinline__ void stx4(float* p, float4 v) {
  asm volatile("st.relaxed.gpu.global.v4.f32 [%0], {%1,%2,%3,%4};" ::"l"(p), "f"(nz(v.x)), "f"(nz(v.y)), "f"(nz(v.z)), "f"(nz(v.w)) : "memory");
}
__device__ __forceinline__ void stx2(float* p, float a, float b) {
  asm volatile("st.relaxed.gpu.global.v2.f32 [%0], {%1,%2};" ::"l"(p), "f"(nz(a)), "f"(nz(b)) : "memory");
}
__device__ __forceinline__ void stx1(float* p, float a) {
  asm volatile("st.relaxed.gpu.global.f32 [%0], %1;" ::"l"(p), "f"(nz(a)) : "memory");
}
__device__ __forceinline__ void clr4(float* p) {
  asm volatile("st.relaxed.gpu.global.v4.f32 [%0], {%1,%1,%1,%1};" ::"l"(p), "f"(0.0f) : "memory");
}
__device__ __forceinline__ bool full4(const float4& v) {
  return __float_as_uint(v.x) != 0u && __float_as_uint(v.y) != 0u && __float_as_uint(v.z) != 0u && __float_as_uint(v.w) != 0u;
}
__device__ __forceinline__ void gather18(float4 (&v)[18], const float* po, const float* pml) {
#pragma unroll
  for (int k = 0; k < 18; k++) v[k] = ldx4(k < 16 ? po + k * 1024 : pml + (k - 16) * 128);
  for (int it = 0;; it++) {
    bool ok = true;
#pragma unroll
    for (int k = 0; k < 18; k++) ok = ok && full4(v[k]);
    if (__all_sync(0xffffffffu, ok)) break;
    if (it > kSpinLimit) KTRAP();
    __nanosleep(40);
#pragma unroll
    for (int k = 0; k < 18; k++)
      if (!full4(v[k])) v[k] = ldx4(k < 16 ? po + k * 1024 : pml + (k - 16) * 128);
  }
}

__device__ __forceinline__ void gather5(float4 (&v)[5], const float* po, const float* pml) {
  for (int it = 0;; it++) {
    bool ok = true;
#pragma unroll
    for (int k = 0; k < 5; k++) ok = ok && full4(v[k]);
    if (__all_sync(0xffffffffu, ok)) break;
    if (it > kSpinLimit) KTRAP();
#pragma unroll
    for (int k = 0; k < 5; k++)
      if (!full4(v[k])) v[k] = ldx4(k < 4 ? po + k * 1024 : pml);
  }
}

__device__ __forceinline__ void load_wo(uint32_t (&a)[18][4], uint32_t base, int w, int lane) {
  const uint32_t wl = ((lane & 7) + (lane >> 4) * 8) * 128 + ((((lane >> 3) & 1) ^ (lane & 7)) << 4);
#pragma unroll
  for (int mt = 0; mt < 9; mt++) {
    const int tile = w * 9 + mt;
    const uint32_t ad = base + (tile >> 2) * 4096 + (wl ^ ((tile & 3) << 5));
    ldsm4t(a[2 * mt], ad);
    ldsm4t(a[2 * mt + 1], ad + 2048);
  }
}

struct Maps {
  CUtensorMap k, v, wq, wo, wg, wu, wd, sp;
};

__global__ void __launch_bounds__(kThreads, 1)
fused_decode_kernel(const __grid_constant__ Maps maps, const __nv_bfloat16* __restrict__ x,
                    const char* __restrict__ wqp, const char* __restrict__ wgp, const char* __restrict__ wup,
                    const char* __restrict__ wdp, __nv_bfloat16* __restrict__ out) {
  if (threadIdx.x == 224 && blockIdx.x < kSliceCtas)
    asm volatile("cp.async.bulk.prefetch.L2.global [%0], %1;" ::"l"(wqp + (size_t)blockIdx.x * 36864), "r"(36864) : "memory");
  extern __shared__ unsigned char smem_dyn[];
  unsigned char* sm = smem_dyn + ((1024u - (smem_u32(smem_dyn) & 1023u)) & 1023u);
  const uint32_t sb = smem_u32(sm);
  const int tid = threadIdx.x, warp = tid >> 5, lane = tid & 31;
  const int cta = blockIdx.x, G = gridDim.x;
  const uint32_t barFull = sb + kOffBar, barEmpty = barFull + kSlots * 8, barInfo = barEmpty + kSlots * 8;
  const uint32_t barMfull = barInfo + kSlots * 8, barMempty = barMfull + 16;
  const uint32_t barWq = barMempty + 16, barWo = barWq + 8, barD = barWo + 8, barQ = barD + 8, barQok = barQ + 8;
  const uint32_t barFree = barQok + 8;
  volatile int* info = reinterpret_cast<volatile int*>(sm + kOffInfo);
  constexpr int kLastBatch = kNAtt - kHKV * kItemsPerPair;

  uint2 xr[9];
  if (warp < 4) {
    const uint2* xp = reinterpret_cast<const uint2*>(x + (warp * 2 + (lane >> 4)) * kD) + (lane & 15);
#pragma unroll
    for (int i = 0; i < 9; i++) xr[i] = __ldg(xp + i * 16);
  }
  if (warp == 5 && lane < 8)
    asm volatile("prefetch.tensormap [%0];" ::"l"(reinterpret_cast<const CUtensorMap*>(&maps) + lane) : "memory");
  unsigned nextDyn = 0;
  uint64_t pol = 0;
  if (tid == 128) {
    TS(0);
    nextDyn = atom_add(&g_ctr.claim, 1);
    for (int i = 0; i < 3 * kSlots; i++) mbar_init(barFull + i * 8, 1);
    mbar_init(barMfull, 4); mbar_init(barMfull + 8, 4);
    mbar_init(barMempty, 1); mbar_init(barMempty + 8, 1);
    mbar_init(barWq, 1); mbar_init(barWo, 1); mbar_init(barD, 4); mbar_init(barQ, 4); mbar_init(barQok, 1);
    for (int i = 0; i < 6; i++) mbar_init(barFree + i * 8, 1);
    asm volatile("fence.mbarrier_init.release.cluster;" ::: "memory");
    asm volatile("createpolicy.fractional.L2::" KPOL ".b64 %0, 1.0;" : "=l"(pol));
    if (cta < kSliceCtas) {
      mbar_expect_tx(barWq, 36864);
#pragma unroll
      for (int w = 0; w < 4; w++) tma2d(sb + kOffW + w * 9216, &maps.wq, cta * 32, w * 144, barWq, pol);
    }
    TS(19);
#pragma unroll
    for (int w = 0; w < KFIRST; w++) {
      info[w] = cta;
      mbar_arrive(barInfo + w * 8);
      mbar_expect_tx(barFull + w * 8, 9216);
      tma2d(sb + kOffRing + w * kSlotBytes, w < 4 ? &maps.wg : &maps.wu, cta * 32, (w & 3) * 144, barFull + w * 8, pol);
    }
  }
  __syncthreads();

  if (warp >= 4) {
  if (warp == 4) {
    if (lane == 0) {
      int item = cta, k = 0, n = KFIRST;
      while (true) {
        const int nsub = item < kNFfn ? 12 : 4;
        int lim = kSlots;
        if (item < kNFfn) lim = KINFLF;
        else if (item < kNFfn + KHEADITEMS || (item >= kNItems - KTAILITEMS && item < kNItems)) lim = KINFL;
#pragma unroll 1
        for (int w = k == 0 ? KFIRST : 0; w < nsub; w++, n++) {
          if (lim < kSlots && n >= lim) mbar_wait(barFull + ((n - lim) & (kSlots - 1)) * 8, ((n - lim) / kSlots) & 1);
          const int slot = n & (kSlots - 1);
          mbar_wait(barEmpty + slot * 8, ((n / kSlots) & 1) ^ 1);
          if (KCLAIMAT > 0 && k > 0 && w == KCLAIMAT && item < kNItems) nextDyn = atom_add(&g_ctr.claim, 1);
          info[slot] = item;
          mbar_arrive(barInfo + slot * 8);
          const uint32_t fb = barFull + slot * 8;
          const uint32_t dst = sb + kOffRing + slot * kSlotBytes;
          if (item >= kNFfn) {
            if (item < kNItems) {
              mbar_expect_tx(fb, kSlotBytes);
              const int a = item - kNFfn;
              const int row = ((a & ~(KILV - 1)) * 4 + w * KILV + (a & (KILV - 1))) * 32;
              tma3d(dst, &maps.k, 0, row, 0, fb, pol);
              tma3d(dst + 8192, &maps.v, 0, row, 0, fb, pol);
            }
          } else {
            mbar_expect_tx(fb, 9216);
            const int c = (w & 3) * 144;
            if (w < 8) tma2d(dst, w < 4 ? &maps.wg : &maps.wu, item * 32, c, fb, pol);
            else tma2d(dst, &maps.wd, c, item * 32, fb, pol);
          }
        }
        if (item >= kNItems) break;
        if (++k < kStaticItems) {
          item = cta + k * G;
        } else {
          item = (int)nextDyn + kStaticItems * G;
          if (KCLAIMAT == 0 && item < kNItems) nextDyn = atom_add(&g_ctr.claim, 1);
        }
      }
      if (cta < kSliceCtas) {
        mbar_wait(barFull + ((n - KWOLAND) & (kSlots - 1)) * 8, ((n - KWOLAND) / kSlots) & 1);
        mbar_expect_tx(barWo, 36864);
        tma4d(sb + kOffW, &maps.wo, 0, (cta & 7) * 16, (cta >> 3) * 2, 0, barWo, pol);
      }
      TS(3);
    }
  } else if (warp == 5) {
    const float* mb = reinterpret_cast<const float*>(sm + kOffMbuf);
    int pend = -1;
    int batch = 0;
    if (lane == 0) {
      if (cta < kSliceCtas) {
        mbar_wait(barQ, 0);
        red_release(&g_ctr.qready, 1);
        TS(10);
      }
      poll_ge(&g_ctr.qready, kSliceCtas, 50);
      mbar_arrive(barQok);
      TS(1);
    }
    __syncwarp();
    for (int kk = 0;; kk++) {
      const int buf = kk & 1;
      mbar_wait(barMfull + buf * 8, (kk >> 1) & 1);
      const float* p = mb + buf * 4 * kMbufStride;
      const int item = __float_as_int(p[260]);
      if (pend >= 0 && lane == 0) red_release(&g_ctr.done[pend * 32], 1);
      if (item < 0) break;
      if ((item >> 10) != batch) {
        batch = item >> 10;
        if (batch >= 2) mbar_wait(barFree + (batch - 2) * 8, 0);
      }
      float4 ml[4];
#pragma unroll
      for (int w = 0; w < 4; w++) ml[w] = *reinterpret_cast<const float4*>(p + w * kMbufStride + 256);
      const float M0 = fmaxf(fmaxf(ml[0].x, ml[1].x), fmaxf(ml[2].x, ml[3].x));
      const float M1 = fmaxf(fmaxf(ml[0].z, ml[1].z), fmaxf(ml[2].z, ml[3].z));
      float4 a = make_float4(0.f, 0.f, 0.f, 0.f), b = a;
      float L0 = 0.f, L1 = 0.f;
#pragma unroll
      for (int w = 0; w < 4; w++) {
        const float s0 = ex2(ml[w].x - M0), s1 = ex2(ml[w].z - M1);
        L0 = fmaf(s0, ml[w].y, L0);
        L1 = fmaf(s1, ml[w].w, L1);
        const float4 u = *reinterpret_cast<const float4*>(p + w * kMbufStride + lane * 4);
        const float4 v = *reinterpret_cast<const float4*>(p + w * kMbufStride + 128 + lane * 4);
        a.x = fmaf(s0, u.x, a.x); a.y = fmaf(s1, u.y, a.y); a.z = fmaf(s0, u.z, a.z); a.w = fmaf(s1, u.w, a.w);
        b.x = fmaf(s0, v.x, b.x); b.y = fmaf(s1, v.y, b.y); b.z = fmaf(s0, v.z, b.z); b.w = fmaf(s1, v.w, b.w);
      }
      float* dst = g_po + (size_t)PSLOT(item >> 6) * (kItemsPerPair * 256) + (item & 63) * 256;
      stx4(dst + lane * 4, a);
      stx4(dst + 128 + lane * 4, b);
      if (lane < 8)
        stx4(reinterpret_cast<float*>(g_pml + (PSLOT(item >> 6) * 8 + lane) * kItemsPerPair + (item & 63)), make_float4(M0, L0, M1, L1));
      __syncwarp();
      pend = item >> 6;
      if (lane == 0) mbar_arrive(barMempty + buf * 8);
      if (item >= kLastBatch) pend = -1;
    }
    if (lane == 0) { TS(4); }
  } else {
    const int cw = warp - 6;
    const int ci64 = tid - 192;
    mbar_wait(barQok, 0);
    if (ci64 == 0) {
      mbar_wait(barD, 0);
      red_release(&g_ctr.ddone, 1);
    }
    if (cta < kSliceCtas) {
      if (lane == 0) poll_ge(&g_ctr.ddone, G, 500);
      __syncwarp();
      float* ssum = reinterpret_cast<float*>(sm + kOffSsum);
      if (ci64 < 63) {
        const int q = ci64 % 9, pg = ci64 / 9;
        float4 acc = make_float4(0.f, 0.f, 0.f, 0.f);
#pragma unroll 4
        for (int p = pg; p < G; p += 7) {
          const float4 v = ldx4(g_dp + p * kOutElems + cta * 36 + q * 4);
          acc.x += v.x; acc.y += v.y; acc.z += v.z; acc.w += v.w;
        }
        *reinterpret_cast<float4*>(ssum + pg * 36 + q * 4) = acc;
      }
      float* g7 = reinterpret_cast<float*>(sm + kOffG7);
      if (cta < kRow7Ctas) {
        float acc = 0.f;
#pragma unroll 4
        for (int p = ci64 >> 3; p < G; p += 8) acc += __ldcg(g_dp + p * kOutElems + (cta * 8 + (ci64 & 7)) * 8 + 7);
        g7[ci64] = acc;
      }
      bar_sync(2, 64);
      if (cta < kRow7Ctas && ci64 >= 56) {
        float d = 0.f;
#pragma unroll
        for (int k = 0; k < 8; k++) d += g7[k * 8 + (ci64 & 7)];
        g7[64 + (ci64 & 7)] = bf16r(silu_f(bf16r(d)));
      }
      if (ci64 < 36) {
        float d = 0.f;
#pragma unroll
        for (int k = 0; k < 7; k++) d += ssum[k * 36 + ci64];
        ssum[252 + ci64] = bf16r(silu_f(bf16r(d)));
      }
      const int kvh = cta >> 3, sl = cta & 7;
      float2* wbuf = reinterpret_cast<float2*>(sm + kOffWbuf) + cw * 64;
      __nv_bfloat16* os = reinterpret_cast<__nv_bfloat16*>(sm + kOffOs);
      const int ci = lane >> 3, q4 = lane & 7;
#pragma unroll 1
      for (int b = cw; b < kB; b += 2) {
        const int pair = b * kHKV + kvh;
        if (b == 4 + cw) {
#pragma unroll 2
          for (int k = 0; k < 18; k++) clr4(g_sp + cta * kOutElems + (k * 64 + ci64) * 4);
          const int pair7 = PSLOT(7 * kHKV + kvh);
#pragma unroll 2
          for (int k = 0; k < 8; k++)
            clr4(g_po + ((size_t)pair7 * kItemsPerPair + k * 8 + (ci64 >> 3)) * 256 + sl * 32 + (ci64 & 7) * 4);
          clr4(reinterpret_cast<float*>(g_pml + (pair7 * 8 + sl) * kItemsPerPair + ci64));
          if (cta < kRow7Ctas) {
#pragma unroll
            for (int k = 0; k < 4; k++) clr4(g_s7 + cta * 1024 + (k * 64 + ci64) * 4);
          }
          __syncwarp();
          if (lane == 0) red_release(&g_ctr.zready, 1);
        }
        if (b >= 2 && lane == 0) {
          if (b == 7) poll_ge(&g_ctr.zready, kSliceCtas * 2, 200);
          else poll_ge(&g_ctr.cons[(b - 2) * 32], kSliceCtas, 200);
          mbar_arrive(barFree + (b - 2) * 8);
        }
        if (b == 7) break;
        const float* pml = reinterpret_cast<const float*>(g_pml + (PSLOT(pair) * 8 + sl) * kItemsPerPair);
        if (lane == 0) poll_ge(&g_ctr.done[pair * 32], kItemsPerPair, 300);
        __syncwarp();
        const float* po = g_po + (size_t)PSLOT(pair) * kItemsPerPair * 256 + sl * 32 + q4 * 4 + ci * 256;
        float4 v[18];
        gather18(v, po, pml + lane * 4);
        __syncwarp();
        if (lane == 0 && b < 5) red_release(&g_ctr.cons[b * 32], 1);
        const float4 mlA = v[16], mlB = v[17];
        const float M0 = warp_max(fmaxf(mlA.x, mlB.x)), M1 = warp_max(fmaxf(mlA.z, mlB.z));
        const float wA0 = ex2(mlA.x - M0), wA1 = ex2(mlA.z - M1), wB0 = ex2(mlB.x - M0), wB1 = ex2(mlB.z - M1);
        float L0 = wA0 * mlA.y + wB0 * mlB.y, L1 = wA1 * mlA.w + wB1 * mlB.w;
        wbuf[lane] = make_float2(wA0, wA1);
        wbuf[32 + lane] = make_float2(wB0, wB1);
        __syncwarp();
        float4 acc = make_float4(0.f, 0.f, 0.f, 0.f);
#pragma unroll
        for (int k = 0; k < 16; k++) {
          const float2 w2 = wbuf[k * 4 + ci];
          acc.x = fmaf(w2.x, v[k].x, acc.x); acc.y = fmaf(w2.y, v[k].y, acc.y);
          acc.z = fmaf(w2.x, v[k].z, acc.z); acc.w = fmaf(w2.y, v[k].w, acc.w);
        }
#pragma unroll
        for (int o = 1; o <= 16; o <<= 1) {
          L0 += __shfl_xor_sync(0xffffffffu, L0, o);
          L1 += __shfl_xor_sync(0xffffffffu, L1, o);
          if (o >= 8) {
            acc.x += __shfl_xor_sync(0xffffffffu, acc.x, o); acc.y += __shfl_xor_sync(0xffffffffu, acc.y, o);
            acc.z += __shfl_xor_sync(0xffffffffu, acc.z, o); acc.w += __shfl_xor_sync(0xffffffffu, acc.w, o);
          }
        }
        if (lane < 8) {
          const float r0 = 1.0f / L0, r1 = 1.0f / L1;
          *reinterpret_cast<uint32_t*>(os + b * 40 + q4 * 2) = pack_bf16(acc.x * r0, acc.z * r0);
          *reinterpret_cast<uint32_t*>(os + b * 40 + 16 + q4 * 2) = pack_bf16(acc.y * r1, acc.w * r1);
        }
        __syncwarp();
      }
      if (lane == 0) { TS(5 + cw); }
      __syncwarp();
      if (cta < kRow7Ctas) bar_arrive(4, 192);
    } else if (lane == 0) {
      for (int b = 2 + cw; b < kB; b += 2) {
        if (b == 7) poll_ge(&g_ctr.zready, kSliceCtas * 2, 500);
        else poll_ge(&g_ctr.cons[(b - 2) * 32], kSliceCtas, 500);
        mbar_arrive(barFree + (b - 2) * 8);
      }
    }
  }
    __syncwarp();
    if (cta < kSliceCtas) {
      const int aw = warp - 4, at = tid - 128;
      const int g = lane >> 2, t = lane & 3;
      const int oe = cta * 36 + at;
      float xv = 0.f;
      if (at < 36) xv = __bfloat162float(x[(oe & 7) * kD + (oe >> 3)]);
      mbar_wait(barFree + 5 * 8, 0);
      mbar_wait(barWo, 0);
      const uint32_t wl = ((lane & 7) + (lane >> 4) * 8) * 128 + ((((lane >> 3) & 1) ^ (lane & 7)) << 4);
      uint32_t a[18][4];
#pragma unroll
      for (int mt = 0; mt < 9; mt++) {
        const int tile = aw * 9 + mt;
        const uint32_t ad = sb + kOffW + (tile >> 2) * 4096 + (wl ^ ((tile & 3) << 5));
        ldsm4t(a[2 * mt], ad);
        ldsm4t(a[2 * mt + 1], ad + 2048);
      }
      bar_sync(3, 128);
      float* stg = reinterpret_cast<float*>(sm + kOffRing) + aw * 1152 + g * 8 + t * 2;
      uint32_t ob[4] = {0u, 0u, 0u, 0u};
      if (g < 7) {
        const __nv_bfloat16* os = reinterpret_cast<const __nv_bfloat16*>(sm + kOffOs) + g * 40 + t * 2;
#pragma unroll
        for (int j = 0; j < 4; j++) ob[j] = *reinterpret_cast<const uint32_t*>(os + j * 8);
      }
#pragma unroll
      for (int mt = 0; mt < 9; mt++) {
        float c[4] = {0.f, 0.f, 0.f, 0.f};
        mma16816(c, a[2 * mt], ob[0], ob[1]);
        mma16816(c, a[2 * mt + 1], ob[2], ob[3]);
#pragma unroll
        for (int h = 0; h < 2; h++) {
          const int e = ((mt * 2 + h) * 8 + g) * 8 + t * 2, u = e / 36;
          stx2(g_sp + ((aw * 32 + u) * kSliceCtas + cta) * 36 + (e - u * 36), c[2 * h], c[2 * h + 1]);
        }
      }
      if (KTMAST == 1) asm volatile("fence.proxy.async;" ::: "memory");
      __syncwarp();
      if (KTMAST == 1 && lane == 0) {
        asm volatile("cp.async.bulk.tensor.3d.global.shared::cta.bulk_group [%0, {%2, %3, %4}], [%1];"
                     ::"l"(&maps.sp), "r"(sb + kOffRing + aw * 4608), "r"(0), "r"(cta), "r"(aw * 32) : "memory");
        asm volatile("cp.async.bulk.commit_group;" ::: "memory");
      }
      if (lane == 0) { TS(40 + aw); }
      if (KDEFER) bar_sync(5, 256);
      const float* fp = g_sp + cta * kOutElems + at * 4;
      const int fcnt = at < 18 ? 10 : (at < 126 ? 9 : 0);
      float4 f[10];
#pragma unroll
      for (int k = 0; k < 10; k++) f[k] = k < fcnt ? ldx4(fp + k * 504) : make_float4(-0.f, -0.f, -0.f, -0.f);
      for (int it = 0;; it++) {
        bool ok = true;
#pragma unroll
        for (int k = 0; k < 10; k++) ok = ok && full4(f[k]);
        if (__all_sync(0xffffffffu, ok)) break;
        if (it > kSpinLimit) KTRAP();
        __nanosleep(KAUXSLEEP);
#pragma unroll
        for (int k = 0; k < 10; k++)
          if (!full4(f[k])) f[k] = ldx4(fp + k * 504);
      }
      float* fsum = reinterpret_cast<float*>(sm + kOffFsum);
      float4 acc = f[0];
#pragma unroll
      for (int k = 1; k < 10; k++) { acc.x += f[k].x; acc.y += f[k].y; acc.z += f[k].z; acc.w += f[k].w; }
      if (at < 126) *reinterpret_cast<float4*>(fsum + at * 4) = acc;
      bar_sync(3, 128);
      if (at < 36 && (oe & 7) != 7) {
        float s = 0.f;
#pragma unroll
        for (int k = 0; k < 14; k++) s += fsum[k * 36 + at];
        const float gt = reinterpret_cast<const float*>(sm + kOffSsum)[252 + at];
        out[(oe & 7) * kD + (oe >> 3)] = __float2bfloat16_rn(xv + bf16r(bf16r(s) * gt));
      }
      if (lane == 0) asm volatile("cp.async.bulk.wait_group 0;" ::: "memory");
      if (lane == 0) { TS(56 + aw); }
    }
  } else {
    const int g = lane >> 2, t = lane & 3;
    __nv_bfloat16* xn = reinterpret_cast<__nv_bfloat16*>(sm + kOffXn);
    {
      float v[36];
#pragma unroll
      for (int i = 0; i < 9; i++) {
        v[4 * i] = __uint_as_float(xr[i].x << 16);
        v[4 * i + 1] = __uint_as_float(xr[i].x & 0xffff0000u);
        v[4 * i + 2] = __uint_as_float(xr[i].y << 16);
        v[4 * i + 3] = __uint_as_float(xr[i].y & 0xffff0000u);
      }
      float s = 0.f;
#pragma unroll
      for (int i = 0; i < 36; i++) s += v[i];
#pragma unroll
      for (int o = 8; o > 0; o >>= 1) s += __shfl_xor_sync(0xffffffffu, s, o);
      const float mean = s * (1.0f / kD);
      float q = 0.f;
#pragma unroll
      for (int i = 0; i < 36; i++) { const float d = v[i] - mean; q = fmaf(d, d, q); }
#pragma unroll
      for (int o = 8; o > 0; o >>= 1) q += __shfl_xor_sync(0xffffffffu, q, o);
      const float mb = bf16r(mean);
      const float rden = 1.0f / bf16r(sqrtf(bf16r(bf16r(q * (1.0f / kD)) + 1e-5f)));
      __nv_bfloat16* xw = xn + (warp * 2 + (lane >> 4)) * kXnPitch + (lane & 15) * 4;
#pragma unroll
      for (int i = 0; i < 9; i++)
        *reinterpret_cast<uint2*>(xw + i * 64) =
            make_uint2(pack_bf16(bf16r(v[4 * i] - mb) * rden, bf16r(v[4 * i + 1] - mb) * rden),
                       pack_bf16(bf16r(v[4 * i + 2] - mb) * rden, bf16r(v[4 * i + 3] - mb) * rden));
    }
    bar_sync(1, 128);
    if (tid == 0) { TS(18); }
    float* mb = reinterpret_cast<float*>(sm + kOffMbuf);
    const uint32_t r8 = lane & 7;
    const uint32_t guLane = (r8 + (lane >> 4) * 8) * 64 + ((((lane >> 3) & 1) ^ (r8 >> 1)) << 4);
    int slot = warp, item;
    uint32_t fph = 0;
    {
      uint32_t xb[9][2];
#pragma unroll
      for (int ks = 0; ks < 9; ks++) {
        xb[ks][0] = *reinterpret_cast<const uint32_t*>(xn + g * kXnPitch + warp * 144 + ks * 16 + t * 2);
        xb[ks][1] = *reinterpret_cast<const uint32_t*>(xn + g * kXnPitch + warp * 144 + ks * 16 + 8 + t * 2);
      }
      if (cta < kSliceCtas) {
        if (tid == 0) {
          g_ctr.done[cta * 32] = 0;
          if (cta < 8) g_ctr.cons[cta * 32] = 0;
          if (cta == 0) { g_ctr.ddone = 0; g_ctr.zready = 0; g_ctr.exitc = 0; }
        }
        mbar_wait(barWq, 0);
        if (tid == 0) { TS(9); }
        const uint32_t lo = sb + kOffW + warp * 9216;
        uint32_t a[18][4];
#pragma unroll
        for (int i = 0; i < 18; i++) ldsm4t(a[i], lo + (guLane ^ ((i & 1) * 32)) + (i >> 1) * 1024);
        float c[2][4] = {{0.f, 0.f, 0.f, 0.f}, {0.f, 0.f, 0.f, 0.f}};
#pragma unroll
        for (int i = 0; i < 18; i++) mma16816(c[i & 1], a[i], xb[i >> 1][0], xb[i >> 1][1]);
        float* qr = mb + warp * 256;
#pragma unroll
        for (int mt = 0; mt < 2; mt++) {
          *reinterpret_cast<float2*>(qr + (mt * 16 + g) * 8 + t * 2) = make_float2(c[mt][0], c[mt][1]);
          *reinterpret_cast<float2*>(qr + (mt * 16 + 8 + g) * 8 + t * 2) = make_float2(c[mt][2], c[mt][3]);
        }
        bar_sync(1, 128);
        const int b = tid >> 4, cp = tid & 15;
        float q0 = 0.f, q1 = 0.f;
#pragma unroll
        for (int w = 0; w < 4; w++) {
          q0 += mb[w * 256 + (cp * 2) * 8 + b];
          q1 += mb[w * 256 + (cp * 2 + 1) * 8 + b];
        }
        const int col = cta * 32 + cp * 2;
        const int head = col >> 7, d = col & 127;
        const int pos = (head & 1) * 128 + (d >> 5) * 32 + ((d & 7) >> 1) * 8 + ((d >> 4) & 1) * 4 + ((d >> 3) & 1) * 2;
        *reinterpret_cast<uint32_t*>(g_q + (b * kHKV + (head >> 1)) * 256 + pos) = pack_bf16(q0, q1);
        __syncwarp();
        if (lane == 0) mbar_arrive(barQ);
        if (tid == 32) { TS(17); }
      } else {
        bar_sync(1, 128);
      }

      float dacc[9][4];
#pragma unroll
      for (int i = 0; i < 9; i++) dacc[i][0] = dacc[i][1] = dacc[i][2] = dacc[i][3] = 0.f;
      float* red = reinterpret_cast<float*>(sm + kOffXn);
      const uint32_t dnLane = (r8 + (lane >> 4) * 8) * 288 + ((lane >> 3) & 1) * 16;
      while (true) {
        mbar_wait(barInfo + slot * 8, fph);
        item = info[slot];
        if (item >= kNFfn) break;
        uint32_t a[18][4];
        float* rw = red + warp * 512;
#pragma unroll 1
        for (int gu = 0; gu < 2; gu++) {
          mbar_wait(barFull + slot * 8, fph);
          const uint32_t base = sb + kOffRing + slot * kSlotBytes;
#pragma unroll
          for (int i = 0; i < 18; i++) ldsm4t(a[i], base + (guLane ^ ((i & 1) * 32)) + (i >> 1) * 1024);
          float c[2][4] = {{0.f, 0.f, 0.f, 0.f}, {0.f, 0.f, 0.f, 0.f}};
#pragma unroll
          for (int i = 0; i < 18; i++) mma16816(c[i & 1], a[i], xb[i >> 1][0], xb[i >> 1][1]);
#pragma unroll
          for (int mt = 0; mt < 2; mt++) {
            float* r = rw + gu * 256 + (2 * t) * 32 + mt * 16 + g;
            r[0] = c[mt][0]; r[32] = c[mt][1]; r[8] = c[mt][2]; r[40] = c[mt][3];
          }
          __syncwarp();
          if (lane == 0) mbar_arrive(barEmpty + slot * 8);
          slot += 4;
          if (slot >= kSlots) { slot -= kSlots; fph ^= 1; }
        }
        bar_sync(1, 128);
        uint32_t hb[4];
#pragma unroll
        for (int j = 0; j < 4; j++) {
          float2 gs = make_float2(0.f, 0.f), us = gs;
#pragma unroll
          for (int w = 0; w < 4; w++) {
            const float* rr = red + w * 512 + g * 32 + j * 8 + t * 2;
            const float2 a2 = *reinterpret_cast<const float2*>(rr), b2 = *reinterpret_cast<const float2*>(rr + 256);
            gs.x += a2.x; gs.y += a2.y; us.x += b2.x; us.y += b2.y;
          }
          hb[j] = pack_bf16(bf16r(silu_f(bf16r(gs.x))) * bf16r(us.x), bf16r(silu_f(bf16r(gs.y))) * bf16r(us.y));
        }
        mbar_wait(barFull + slot * 8, fph);
        const uint32_t base = sb + kOffRing + slot * kSlotBytes + dnLane;
#pragma unroll
        for (int i = 0; i < 18; i++) ldsm4t(a[i], base + (i >> 1) * 32 + (i & 1) * 4608);
#pragma unroll
        for (int i = 0; i < 18; i++) mma16816(dacc[i >> 1], a[i], hb[(i & 1) * 2], hb[(i & 1) * 2 + 1]);
        bar_sync(1, 128);
        if (lane == 0) mbar_arrive(barEmpty + slot * 8);
        slot += 4;
        if (slot >= kSlots) { slot -= kSlots; fph ^= 1; }
      }
      if (tid == 0) { TS(12); }
      float* dp = g_dp + cta * kOutElems + (warp * 144 + g) * 8 + t * 2;
#pragma unroll
      for (int mt = 0; mt < 9; mt++) {
        *reinterpret_cast<float2*>(dp + mt * 128) = make_float2(dacc[mt][0], dacc[mt][1]);
        *reinterpret_cast<float2*>(dp + mt * 128 + 64) = make_float2(dacc[mt][2], dacc[mt][3]);
      }
      __syncwarp();
      if (lane == 0) mbar_arrive(barD);
      mbar_wait(barQok, 0);
      if (tid == 0) { TS(2); }
    }

    const float kScale = 0.08838834764831845f * 1.4426950408889634f;
    const uint32_t kLane = (r8 + ((lane >> 3) & 1) * 8) * 128 + (((lane >> 4) ^ r8) << 4);
    const uint32_t vLane = 8192 + (r8 + (lane >> 4) * 8) * 128 + ((((lane >> 3) & 1) ^ r8) << 4);
    int kk = 0;
    while (item < kNItems) {
      item -= kNFfn;
      uint4 qv[4];
      if (g < 2) {
        const uint4* qs = reinterpret_cast<const uint4*>(g_q + (item >> 6) * 256 + g * 128 + t * 8);
#pragma unroll
        for (int i = 0; i < 4; i++) qv[i] = qs[i * 4];
      } else {
#pragma unroll
        for (int i = 0; i < 4; i++) qv[i] = make_uint4(0u, 0u, 0u, 0u);
      }
      mbar_wait(barFull + slot * 8, fph);
      const uint32_t base = sb + kOffRing + slot * kSlotBytes;
      uint32_t ka[16][4], va[16][4];
#pragma unroll
      for (int i = 0; i < 16; i++)
        ldsm4(ka[i], base + ((kLane ^ (((i >> 1) & 3) << 5)) + (i >> 3) * 4096 + (i & 1) * 2048));
#pragma unroll
      for (int i = 0; i < 16; i++)
        ldsm4t(va[i], base + ((vLane ^ (((i >> 1) & 3) << 5)) + (i >> 3) * 4096 + (i & 1) * 2048));
      float s[2][4], s2[2][4];
#pragma unroll
      for (int i = 0; i < 4; i++) s[0][i] = s[1][i] = s2[0][i] = s2[1][i] = 0.f;
#pragma unroll
      for (int kp = 0; kp < 4; kp++) {
        mma16816(s[0], ka[4 * kp], qv[kp].x, qv[kp].y);
        mma16816(s[1], ka[4 * kp + 1], qv[kp].x, qv[kp].y);
        mma16816(s2[0], ka[4 * kp + 2], qv[kp].z, qv[kp].w);
        mma16816(s2[1], ka[4 * kp + 3], qv[kp].z, qv[kp].w);
      }
#pragma unroll
      for (int i = 0; i < 4; i++) { s[0][i] += s2[0][i]; s[1][i] += s2[1][i]; }
      float m0 = fmaxf(fmaxf(s[0][0], s[0][2]), fmaxf(s[1][0], s[1][2]));
      float m1 = fmaxf(fmaxf(s[0][1], s[0][3]), fmaxf(s[1][1], s[1][3]));
#pragma unroll
      for (int o = 4; o <= 16; o <<= 1) {
        m0 = fmaxf(m0, __shfl_xor_sync(0xffffffffu, m0, o));
        m1 = fmaxf(m1, __shfl_xor_sync(0xffffffffu, m1, o));
      }
      m0 *= kScale; m1 *= kScale;
      float l0 = 0.f, l1 = 0.f;
      uint32_t pb[2][2];
#pragma unroll
      for (int mt = 0; mt < 2; mt++) {
        const float p0 = ex2(fmaf(s[mt][0], kScale, -m0)), p1 = ex2(fmaf(s[mt][1], kScale, -m1));
        const float p2 = ex2(fmaf(s[mt][2], kScale, -m0)), p3 = ex2(fmaf(s[mt][3], kScale, -m1));
        l0 += p0 + p2; l1 += p1 + p3;
        pb[mt][0] = movmat(pack_bf16(p0, p1));
        pb[mt][1] = movmat(pack_bf16(p2, p3));
      }
      float o_[8][4];
#pragma unroll
      for (int j = 0; j < 8; j++) {
        o_[j][0] = o_[j][1] = o_[j][2] = o_[j][3] = 0.f;
        mma16816(o_[j], va[2 * j], pb[0][0], pb[0][1]);
      }
#pragma unroll
      for (int j = 0; j < 8; j++) mma16816(o_[j], va[2 * j + 1], pb[1][0], pb[1][1]);
#pragma unroll
      for (int o = 4; o <= 16; o <<= 1) {
        l0 += __shfl_xor_sync(0xffffffffu, l0, o);
        l1 += __shfl_xor_sync(0xffffffffu, l1, o);
      }
      const int buf = kk & 1;
      mbar_wait(barMempty + buf * 8, ((kk >> 1) & 1) ^ 1);
      float* p = mb + (buf * 4 + warp) * kMbufStride;
      if (t == 0) {
#pragma unroll
        for (int j = 0; j < 8; j++) {
          *reinterpret_cast<float2*>(p + (j * 16 + g) * 2) = make_float2(o_[j][0], o_[j][1]);
          *reinterpret_cast<float2*>(p + (j * 16 + 8 + g) * 2) = make_float2(o_[j][2], o_[j][3]);
        }
        if (g == 0) {
          *reinterpret_cast<float4*>(p + 256) = make_float4(m0, l0, m1, l1);
          p[260] = __int_as_float(item);
        }
      }
      __syncwarp();
      if (lane == 0) {
        mbar_arrive(barMfull + buf * 8);
        mbar_arrive(barEmpty + slot * 8);
      }
      kk++;
      slot += 4;
      if (slot >= kSlots) { slot -= kSlots; fph ^= 1; }
      mbar_wait(barInfo + slot * 8, fph);
      item = info[slot];
    }
    {
      const int buf = kk & 1;
      mbar_wait(barMempty + buf * 8, ((kk >> 1) & 1) ^ 1);
      if (lane == 0) {
        mb[(buf * 4 + warp) * kMbufStride + 260] = __int_as_float(-1);
        mbar_arrive(barMfull + buf * 8);
        if (warp == 0) red_relaxed(&g_ctr.exitc, 1);
      }
      __syncwarp();
    }
    if (tid == 0) { TS(11); }
    if (lane == 0) { TS(32 + warp); }
    if (cta < kSliceCtas) {
      float xv = 0.f;
      if (tid < 8 && cta < kRow7Ctas) xv = __bfloat162float(x[7 * kD + cta * 8 + tid]);
      mbar_wait(barFree + 5 * 8, 0);
      const int ps = PSLOT(7 * kHKV + (cta >> 3)), sl = cta & 7;
      const int ci = lane >> 3, q4 = lane & 7;
      const float* po = g_po + (ps * kItemsPerPair + warp * 16 + ci) * 256 + sl * 32 + q4 * 4;
      const float* pml = reinterpret_cast<const float*>(g_pml + (ps * 8 + sl) * kItemsPerPair + warp * 16 + (lane & 15));
      float4 v[5];
#pragma unroll
      for (int k = 0; k < 5; k++) v[k] = ldx4(k < 4 ? po + k * 1024 : pml);
      uint32_t a[18][4], ob[4];
      if (KWOFIRST) {
        mbar_wait(barWo, 0);
        load_wo(a, sb + kOffW, warp, lane);
      }
      gather5(v, po, pml);
      if (lane == 0) { TS(36 + warp); }
      float* cb = reinterpret_cast<float*>(sm + kOffCbuf);
      {
        const float M0 = warp_max(v[4].x), M1 = warp_max(v[4].z);
        const float w0 = ex2(v[4].x - M0), w1 = ex2(v[4].z - M1);
        float L0 = w0 * v[4].y, L1 = w1 * v[4].w;
        float4 acc = make_float4(0.f, 0.f, 0.f, 0.f);
#pragma unroll
        for (int k = 0; k < 4; k++) {
          const float a0 = __shfl_sync(0xffffffffu, w0, k * 4 + ci), a1 = __shfl_sync(0xffffffffu, w1, k * 4 + ci);
          acc.x = fmaf(a0, v[k].x, acc.x); acc.y = fmaf(a1, v[k].y, acc.y);
          acc.z = fmaf(a0, v[k].z, acc.z); acc.w = fmaf(a1, v[k].w, acc.w);
        }
#pragma unroll
        for (int o = 1; o <= 16; o <<= 1) {
          if (o <= 8) {
            L0 += __shfl_xor_sync(0xffffffffu, L0, o);
            L1 += __shfl_xor_sync(0xffffffffu, L1, o);
          }
          if (o >= 8) {
            acc.x += __shfl_xor_sync(0xffffffffu, acc.x, o); acc.y += __shfl_xor_sync(0xffffffffu, acc.y, o);
            acc.z += __shfl_xor_sync(0xffffffffu, acc.z, o); acc.w += __shfl_xor_sync(0xffffffffu, acc.w, o);
          }
        }
        if (lane < 8) {
          *reinterpret_cast<float2*>(cb + warp * 40 + q4 * 2) = make_float2(acc.x, acc.z);
          *reinterpret_cast<float2*>(cb + warp * 40 + 16 + q4 * 2) = make_float2(acc.y, acc.w);
          if (lane == 0) *reinterpret_cast<float4*>(cb + warp * 40 + 32) = make_float4(M0, L0, M1, L1);
        }
      }
      if (!KWOFIRST) {
        mbar_wait(barWo, 0);
        load_wo(a, sb + kOffW, warp, lane);
      }
      if (tid == 0) { TS(29); }
      bar_sync(1, 128);
      {
        float4 ml[4];
#pragma unroll
        for (int w = 0; w < 4; w++) ml[w] = *reinterpret_cast<const float4*>(cb + w * 40 + 32);
        const float M0 = fmaxf(fmaxf(ml[0].x, ml[1].x), fmaxf(ml[2].x, ml[3].x));
        const float M1 = fmaxf(fmaxf(ml[0].z, ml[1].z), fmaxf(ml[2].z, ml[3].z));
        float L0 = 0.f, L1 = 0.f;
        float2 o2[4] = {{0.f, 0.f}, {0.f, 0.f}, {0.f, 0.f}, {0.f, 0.f}};
#pragma unroll
        for (int w = 0; w < 4; w++) {
          const float s0 = ex2(ml[w].x - M0), s1 = ex2(ml[w].z - M1);
          L0 = fmaf(s0, ml[w].y, L0);
          L1 = fmaf(s1, ml[w].w, L1);
#pragma unroll
          for (int j = 0; j < 4; j++) {
            const float2 u = *reinterpret_cast<const float2*>(cb + w * 40 + j * 8 + t * 2);
            o2[j].x = fmaf(j < 2 ? s0 : s1, u.x, o2[j].x);
            o2[j].y = fmaf(j < 2 ? s0 : s1, u.y, o2[j].y);
          }
        }
        const float r0 = __frcp_rn(L0), r1 = __frcp_rn(L1);
#pragma unroll
        for (int j = 0; j < 4; j++) ob[j] = pack_bf16(o2[j].x * (j < 2 ? r0 : r1), o2[j].y * (j < 2 ? r0 : r1));
      }
      if (lane == 0) { TS(52 + warp); }
      {
        float c[10][4];
#pragma unroll
        for (int mt = 0; mt < 9; mt++) {
          c[mt][0] = c[mt][1] = c[mt][2] = c[mt][3] = 0.f;
          mma16816(c[mt], a[2 * mt], ob[0], ob[1]);
          mma16816(c[mt], a[2 * mt + 1], ob[2], ob[3]);
        }
        c[9][0] = c[9][2] = 0.f;
        float* s7 = g_s7 + ((warp * 18 + t) * kSliceCtas + cta) * 8 + g;
#pragma unroll
        for (int k = 0; k < 5; k++) {
          const float lo = (t & 1) ? c[2 * k][2] : c[2 * k][0], hi = (t & 1) ? c[2 * k + 1][2] : c[2 * k + 1][0];
          if (k < 4 || t < 2) stx1(s7 + k * 4 * kSliceCtas * 8, (t & 2) ? hi : lo);
        }
      }
      if (KDEFER) bar_arrive(5, 256);
      if (lane == 0) { TS(44 + warp); }
      if (tid == 0) { TS(7); TS(8); }
      if (cta < kRow7Ctas) {
        const float* hp = g_s7 + cta * 1024 + tid * 4;
        float4 f0 = ldx4(hp), f1 = ldx4(hp + 512);
        for (int it = 0; !__all_sync(0xffffffffu, full4(f0) && full4(f1)); it++) {
          if (it > kSpinLimit) KTRAP();
          if (!full4(f0)) f0 = ldx4(hp);
          if (!full4(f1)) f1 = ldx4(hp + 512);
        }
        if (lane == 0) { TS(48 + warp); }
        float* g7 = reinterpret_cast<float*>(sm + kOffG7);
        float4 h = make_float4(f0.x + f1.x, f0.y + f1.y, f0.z + f1.z, f0.w + f1.w);
#pragma unroll
        for (int o = 2; o <= 16; o <<= 1) {
          h.x += __shfl_xor_sync(0xffffffffu, h.x, o); h.y += __shfl_xor_sync(0xffffffffu, h.y, o);
          h.z += __shfl_xor_sync(0xffffffffu, h.z, o); h.w += __shfl_xor_sync(0xffffffffu, h.w, o);
        }
        if (lane < 2) *reinterpret_cast<float4*>(g7 + 72 + warp * 8 + lane * 4) = h;
        bar_sync(4, 192);
        if (tid < 8) {
          const float s = (g7[72 + tid] + g7[80 + tid]) + (g7[88 + tid] + g7[96 + tid]);
          out[7 * kD + cta * 8 + tid] = __float2bfloat16_rn(xv + bf16r(bf16r(s) * g7[64 + tid]));
        }
      }
      if (cta == 0 && tid == 96) {
        poll_ge(&g_ctr.exitc, G, 20);
        g_ctr.claim = 0;
        g_ctr.qready = 0;
      }
    }
    if (tid == 0) { TS(14); }
  }
}

typedef CUresult (*EncodeFn)(CUtensorMap*, CUtensorMapDataType, cuuint32_t, void*, const cuuint64_t*,
                             const cuuint64_t*, const cuuint32_t*, const cuuint32_t*, CUtensorMapInterleave,
                             CUtensorMapSwizzle, CUtensorMapL2promotion, CUtensorMapFloatOOBfill);

void encode(EncodeFn fn, CUtensorMap* m, const void* base, int rank, const cuuint64_t* dims, const cuuint64_t* strides,
            const cuuint32_t* box, CUtensorMapSwizzle sw,
            CUtensorMapDataType dt = CU_TENSOR_MAP_DATA_TYPE_BFLOAT16, int promo = KPROMOW) {
  const cuuint32_t es[4] = {1, 1, 1, 1};
  fn(m, dt, rank, const_cast<void*>(base), dims, strides, box, es,
     CU_TENSOR_MAP_INTERLEAVE_NONE, sw, (CUtensorMapL2promotion)promo, CU_TENSOR_MAP_FLOAT_OOB_FILL_NONE);
}

}

extern "C" void kernel_launch(void* const* d_in, const int* in_sizes, int n_in, void* d_out, int out_size) {
  (void)in_sizes; (void)n_in; (void)out_size;
  static EncodeFn fn = nullptr;
  static int sms = 0;
  if (!fn) {
    void* p = nullptr;
    cudaDriverEntryPointQueryResult qr;
    cudaGetDriverEntryPoint("cuTensorMapEncodeTiled", &p, cudaEnableDefault, &qr);
    fn = (EncodeFn)p;
    int dev = 0;
    cudaGetDevice(&dev);
    cudaDeviceGetAttribute(&sms, cudaDevAttrMultiProcessorCount, dev);
    cudaFuncSetAttribute(fused_decode_kernel, cudaFuncAttributeMaxDynamicSharedMemorySize, kSmemBytes);
  }
  Maps maps;
  {
    const cuuint64_t dims[3] = {64, (cuuint64_t)kPairs * kSK, 2}, str[2] = {256, 128};
    const cuuint32_t box[3] = {64, 32, 2};
    encode(fn, &maps.k, d_in[1], 3, dims, str, box, CU_TENSOR_MAP_SWIZZLE_128B, CU_TENSOR_MAP_DATA_TYPE_BFLOAT16, KPROMOKV);
    encode(fn, &maps.v, d_in[2], 3, dims, str, box, CU_TENSOR_MAP_SWIZZLE_128B, CU_TENSOR_MAP_DATA_TYPE_BFLOAT16, KPROMOKV);
  }
  {
    const cuuint64_t dims[2] = {4096, kD}, str[1] = {8192};
    const cuuint32_t box[2] = {32, 144};
    encode(fn, &maps.wq, d_in[3], 2, dims, str, box, CU_TENSOR_MAP_SWIZZLE_64B);
  }
  {
    const cuuint64_t dims[4] = {64, 128, 32, 9}, str[3] = {kD * 2, 128 * kD * 2, 128};
    const cuuint32_t box[4] = {64, 16, 2, 9};
    encode(fn, &maps.wo, d_in[4], 4, dims, str, box, CU_TENSOR_MAP_SWIZZLE_128B, CU_TENSOR_MAP_DATA_TYPE_BFLOAT16, KPROMOO);
  }
  {
    const cuuint64_t dims[2] = {kF, kD}, str[1] = {kF * 2};
    const cuuint32_t box[2] = {32, 144};
    encode(fn, &maps.wg, d_in[6], 2, dims, str, box, CU_TENSOR_MAP_SWIZZLE_64B);
    encode(fn, &maps.wu, d_in[7], 2, dims, str, box, CU_TENSOR_MAP_SWIZZLE_64B);
  }
  {
    const cuuint64_t dims[2] = {kD, kF}, str[1] = {kD * 2};
    const cuuint32_t box[2] = {144, 32};
    encode(fn, &maps.wd, d_in[8], 2, dims, str, box, CU_TENSOR_MAP_SWIZZLE_NONE, CU_TENSOR_MAP_DATA_TYPE_BFLOAT16, KPROMOD);
  }
  {
    void* sp = nullptr;
    cudaGetSymbolAddress(&sp, g_sp);
    const cuuint64_t dims[3] = {36, kSliceCtas, kSliceCtas}, str[2] = {144, kOutElems * 4};
    const cuuint32_t box[3] = {36, 1, 32};
    encode(fn, &maps.sp, sp, 3, dims, str, box, CU_TENSOR_MAP_SWIZZLE_NONE, CU_TENSOR_MAP_DATA_TYPE_FLOAT32);
  }
  int grid = sms < kMaxCtas ? sms : kMaxCtas;
  fused_decode_kernel<<<grid, kThreads, kSmemBytes>>>(maps, (const __nv_bfloat16*)d_in[0], (const char*)d_in[3],
                                                      (const char*)d_in[6], (const char*)d_in[7], (const char*)d_in[8],
                                                      (__nv_bfloat16*)d_out);
}
```

```cpp
#include <cuda_runtime.h>
#include <cuda_bf16.h>
#include <cuda.h>
#include <stdint.h>

namespace {

constexpr int kB = 8, kD = 576, kHKV = 16, kSK = 8192, kF = 4608;
constexpr int kPairs = kB * kHKV;
constexpr int kItemRows = 128;
constexpr int kItemsPerPair = kSK / kItemRows;
constexpr int kNAtt = kPairs * kItemsPerPair;
constexpr int kNFfn = kF / 32;
constexpr int kNItems = kNAtt + kNFfn;
constexpr int kSlots = 8;
constexpr int kSlotBytes = 16384;
constexpr int kMaxCtas = kNFfn;
constexpr int kSliceCtas = 128;
constexpr int kRow7Ctas = 72;
constexpr int kThreads = 256;
constexpr int kOutElems = kB * kD;

constexpr int kOffRing = 0;
constexpr int kOffW = kOffRing + kSlots * kSlotBytes;
constexpr int kOffXn = kOffW + 36864;
constexpr int kXnPitch = 584;
constexpr int kOffMbuf = kOffXn + kB * kXnPitch * 2;
constexpr int kMbufStride = 264;
constexpr int kOffOs = kOffMbuf + 2 * 4 * kMbufStride * 4;
constexpr int kOffWbuf = kOffOs + 8 * 40 * 2;
constexpr int kOffFsum = kOffWbuf + 2 * 64 * 8;
constexpr int kOffSsum = kOffFsum + 14 * 36 * 4;
constexpr int kOffG7 = kOffSsum + 8 * 36 * 4;
constexpr int kOffCbuf = kOffG7 + 104 * 4;
constexpr int kOffInfo = kOffCbuf + 4 * 40 * 4;
constexpr int kOffBar = kOffInfo + 64;
constexpr int kNumBars = 3 * kSlots + 8 + 6;
constexpr int kSmemBytes = kOffBar + kNumBars * 8 + 1024;
static_assert(kSmemBytes <= 232448, "smem");

constexpr int kPartSlots = 48;
__device__ __forceinline__ int PSLOT(int pair) { return pair >= 112 ? pair - 80 : (pair & 31); }

struct Counters {
  unsigned claim;
  unsigned qready; unsigned pad1[30];
  unsigned ddone;  unsigned pad2[31];
  unsigned zready; unsigned pad3[31];
  unsigned exitc;  unsigned pad4[31];
  unsigned cons[8 * 32];
  unsigned done[kPairs * 32];
};

__device__ Counters g_ctr;
__device__ __align__(128) __nv_bfloat16 g_q[kPairs * 256];
__device__ __align__(128) float g_po[kPartSlots * kItemsPerPair * 256];
__device__ __align__(128) float4 g_pml[kPartSlots * 8 * kItemsPerPair];
__device__ __align__(128) float g_sp[kSliceCtas * kOutElems];
__device__ __align__(128) float g_s7[kRow7Ctas * kSliceCtas * 8];
__device__ __align__(128) float g_dp[kMaxCtas * kOutElems];
#define TS(i)

constexpr int kSpinLimit = 1 << 21;

__device__ __forceinline__ uint32_t smem_u32(const void* p) { return (uint32_t)__cvta_generic_to_shared(p); }
__device__ __forceinline__ void mbar_init(uint32_t bar, uint32_t cnt) {
  asm volatile("mbarrier.init.shared::cta.b64 [%0], %1;" ::"r"(bar), "r"(cnt) : "memory");
}
__device__ __forceinline__ void mbar_expect_tx(uint32_t bar, uint32_t bytes) {
  asm volatile("mbarrier.arrive.expect_tx.shared::cta.b64 _, [%0], %1;" ::"r"(bar), "r"(bytes) : "memory");
}
__device__ __forceinline__ void mbar_arrive(uint32_t bar) {
  asm volatile("mbarrier.arrive.shared::cta.b64 _, [%0];" ::"r"(bar) : "memory");
}
__device__ __forceinline__ void mbar_wait(uint32_t bar, uint32_t parity) {
  uint32_t done;
  int it = 0;
  do {
    asm volatile(
        "{\n.reg .pred p;\nmbarrier.try_wait.parity.shared::cta.b64 p, [%1], %2;\nselp.u32 %0, 1, 0, p;\n}"
        : "=r"(done) : "r"(bar), "r"(parity) : "memory");
    if (++it > kSpinLimit) __trap();
  } while (!done);
}
__device__ __forceinline__ bool mbar_test(uint32_t bar, uint32_t parity) {
  uint32_t done;
  asm volatile(
      "{\n.reg .pred p;\nmbarrier.test_wait.parity.shared::cta.b64 p, [%1], %2;\nselp.u32 %0, 1, 0, p;\n}"
      : "=r"(done) : "r"(bar), "r"(parity) : "memory");
  return done != 0;
}
__device__ __forceinline__ void tma2d(uint32_t dst, const CUtensorMap* m, int c0, int c1, uint32_t bar, uint64_t pol) {
  asm volatile(
      "cp.async.bulk.tensor.2d.shared::cluster.global.mbarrier::complete_tx::bytes.L2::cache_hint [%0], [%1, {%3, %4}], [%2], %5;"
      ::"r"(dst), "l"(m), "r"(bar), "r"(c0), "r"(c1), "l"(pol) : "memory");
}
__device__ __forceinline__ void tma3d(uint32_t dst, const CUtensorMap* m, int c0, int c1, int c2, uint32_t bar, uint64_t pol) {
  asm volatile(
      "cp.async.bulk.tensor.3d.shared::cluster.global.mbarrier::complete_tx::bytes.L2::cache_hint [%0], [%1, {%3, %4, %5}], [%2], %6;"
      ::"r"(dst), "l"(m), "r"(bar), "r"(c0), "r"(c1), "r"(c2), "l"(pol) : "memory");
}
__device__ __forceinline__ void tma4d(uint32_t dst, const CUtensorMap* m, int c0, int c1, int c2, int c3, uint32_t bar, uint64_t pol) {
  asm volatile(
      "cp.async.bulk.tensor.4d.shared::cluster.global.mbarrier::complete_tx::bytes.L2::cache_hint [%0], [%1, {%3, %4, %5, %6}], [%2], %7;"
      ::"r"(dst), "l"(m), "r"(bar), "r"(c0), "r"(c1), "r"(c2), "r"(c3), "l"(pol) : "memory");
}
__device__ __forceinline__ void cp_async16(uint32_t dst, const void* src) {
  asm volatile("cp.async.cg.shared.global.L2::128B [%0], [%1], 16;" ::"r"(dst), "l"(src) : "memory");
}
__device__ __forceinline__ void ldsm4(uint32_t (&r)[4], uint32_t addr) {
  asm volatile("ldmatrix.sync.aligned.m8n8.x4.shared.b16 {%0,%1,%2,%3}, [%4];"
               : "=r"(r[0]), "=r"(r[1]), "=r"(r[2]), "=r"(r[3]) : "r"(addr) : "memory");
}
__device__ __forceinline__ void ldsm4t(uint32_t (&r)[4], uint32_t addr) {
  asm volatile("ldmatrix.sync.aligned.m8n8.x4.trans.shared.b16 {%0,%1,%2,%3}, [%4];"
               : "=r"(r[0]), "=r"(r[1]), "=r"(r[2]), "=r"(r[3]) : "r"(addr) : "memory");
}
__device__ __forceinline__ void mma16816(float (&c)[4], const uint32_t (&a)[4], uint32_t b0, uint32_t b1) {
  asm(
      "mma.sync.aligned.m16n8k16.row.col.f32.bf16.bf16.f32 {%0,%1,%2,%3}, {%4,%5,%6,%7}, {%8,%9}, {%0,%1,%2,%3};"
      : "+f"(c[0]), "+f"(c[1]), "+f"(c[2]), "+f"(c[3])
      : "r"(a[0]), "r"(a[1]), "r"(a[2]), "r"(a[3]), "r"(b0), "r"(b1));
}
__device__ __forceinline__ uint32_t movmat(uint32_t a) {
  uint32_t d;
  asm volatile("movmatrix.sync.aligned.m8n8.trans.b16 %0, %1;" : "=r"(d) : "r"(a));
  return d;
}
__device__ __forceinline__ float ex2(float x) {
  float y;
  asm("ex2.approx.ftz.f32 %0, %1;" : "=f"(y) : "f"(x));
  return y;
}
__device__ __forceinline__ uint32_t pack_bf16(float lo, float hi) {
  uint32_t r;
  asm("cvt.rn.bf16x2.f32 %0, %1, %2;" : "=r"(r) : "f"(hi), "f"(lo));
  return r;
}
__device__ __forceinline__ float bf16r(float x) { return __bfloat162float(__float2bfloat16_rn(x)); }
__device__ __forceinline__ float silu_f(float x) { return x / (1.0f + __expf(-x)); }
__device__ __forceinline__ float warp_max(float x) {
  int i = __float_as_int(x);
  i ^= (i >> 31) & 0x7fffffff;
  i = __reduce_max_sync(0xffffffffu, i);
  i ^= (i >> 31) & 0x7fffffff;
  return __int_as_float(i);
}
__device__ __forceinline__ void bar_sync(int id, int n) { asm volatile("bar.sync %0, %1;" ::"r"(id), "r"(n) : "memory"); }
__device__ __forceinline__ void bar_arrive(int id, int n) { asm volatile("bar.arrive %0, %1;" ::"r"(id), "r"(n) : "memory"); }
__device__ __forceinline__ void red_release(unsigned* p, unsigned v) {
  asm volatile("red.release.gpu.global.add.u32 [%0], %1;" ::"l"(p), "r"(v) : "memory");
}
__device__ __forceinline__ void red_relaxed(unsigned* p, unsigned v) {
  asm volatile("red.relaxed.gpu.global.add.u32 [%0], %1;" ::"l"(p), "r"(v) : "memory");
}
__device__ __forceinline__ unsigned ld_acquire(const unsigned* p) {
  unsigned v;
  asm volatile("ld.acquire.gpu.global.u32 %0, [%1];" : "=r"(v) : "l"(p) : "memory");
  return v;
}
__device__ __forceinline__ unsigned atom_add(unsigned* p, unsigned v) {
  unsigned r;
  asm volatile("atom.relaxed.gpu.global.add.u32 %0, [%1], %2;" : "=r"(r) : "l"(p), "r"(v) : "memory");
  return r;
}
__device__ __forceinline__ void poll_ge(const unsigned* p, unsigned target, unsigned sleep_ns) {
  int it = 0;
  while (ld_acquire(p) < target) {
    if (sleep_ns) __nanosleep(sleep_ns);
    if (++it > kSpinLimit) __trap();
  }
}
__device__ __forceinline__ float4 ldx4(const float* p) {
  float4 v;
  asm volatile("ld.relaxed.gpu.global.v4.f32 {%0,%1,%2,%3}, [%4];" : "=f"(v.x), "=f"(v.y), "=f"(v.z), "=f"(v.w) : "l"(p) : "memory");
  return v;
}
__device__ __forceinline__ float nz(float v) { return __float_as_uint(v) == 0u ? -0.0f : v; }
__device__ __forceinline__ void stx4(float* p, float4 v) {
  asm volatile("st.relaxed.gpu.global.v4.f32 [%0], {%1,%2,%3,%4};" ::"l"(p), "f"(nz(v.x)), "f"(nz(v.y)), "f"(nz(v.z)), "f"(nz(v.w)) : "memory");
}
__device__ __forceinline__ void stx2(float* p, float a, float b) {
  asm volatile("st.relaxed.gpu.global.v2.f32 [%0], {%1,%2};" ::"l"(p), "f"(nz(a)), "f"(nz(b)) : "memory");
}
__device__ __forceinline__ void stx1(float* p, float a) {
  asm volatile("st.relaxed.gpu.global.f32 [%0], %1;" ::"l"(p), "f"(nz(a)) : "memory");
}
__device__ __forceinline__ void clr4(float* p) {
  asm volatile("st.relaxed.gpu.global.v4.f32 [%0], {%1,%1,%1,%1};" ::"l"(p), "f"(0.0f) : "memory");
}
__device__ __forceinline__ bool full4(const float4& v) {
  return __float_as_uint(v.x) != 0u && __float_as_uint(v.y) != 0u && __float_as_uint(v.z) != 0u && __float_as_uint(v.w) != 0u;
}
__device__ __forceinline__ void gather18(float4 (&v)[18], const float* po, const float* pml) {
#pragma unroll
  for (int k = 0; k < 18; k++) v[k] = ldx4(k < 16 ? po + k * 1024 : pml + (k - 16) * 128);
  for (int it = 0;; it++) {
    bool ok = true;
#pragma unroll
    for (int k = 0; k < 18; k++) ok = ok && full4(v[k]);
    if (__all_sync(0xffffffffu, ok)) break;
    if (it > kSpinLimit) __trap();
    __nanosleep(40);
#pragma unroll
    for (int k = 0; k < 18; k++)
      if (!full4(v[k])) v[k] = ldx4(k < 16 ? po + k * 1024 : pml + (k - 16) * 128);
  }
}

__device__ __forceinline__ void load_wo(uint32_t (&a)[18][4], uint32_t base, int w, int lane) {
  const uint32_t wl = ((lane & 7) + (lane >> 4) * 8) * 128 + ((((lane >> 3) & 1) ^ (lane & 7)) << 4);
#pragma unroll
  for (int mt = 0; mt < 9; mt++) {
    const int tile = w * 9 + mt;
    const uint32_t ad = base + (tile >> 2) * 4096 + (wl ^ ((tile & 3) << 5));
    ldsm4t(a[2 * mt], ad);
    ldsm4t(a[2 * mt + 1], ad + 2048);
  }
}

struct Maps {
  CUtensorMap wg, wu, wd, k, v, wo;
};

__global__ void __launch_bounds__(kThreads, 1)
fused_decode_kernel(const __grid_constant__ Maps maps, const __nv_bfloat16* __restrict__ x,
                    const char* __restrict__ wqp, __nv_bfloat16* __restrict__ out) {
  if (threadIdx.x == 224 && blockIdx.x < kSliceCtas)
    asm volatile("cp.async.bulk.prefetch.L2.global [%0], %1;" ::"l"(wqp + (size_t)blockIdx.x * 36864), "r"(36864) : "memory");
  extern __shared__ unsigned char smem_dyn[];
  unsigned char* sm = smem_dyn + ((1024u - (smem_u32(smem_dyn) & 1023u)) & 1023u);
  const uint32_t sb = smem_u32(sm);
  const int tid = threadIdx.x, warp = tid >> 5, lane = tid & 31;
  const int cta = blockIdx.x, G = gridDim.x;
  const uint32_t barFull = sb + kOffBar, barEmpty = barFull + kSlots * 8, barInfo = barEmpty + kSlots * 8;
  const uint32_t barMfull = barInfo + kSlots * 8, barMempty = barMfull + 16;
  const uint32_t barWo = barMempty + 16, barD = barWo + 8, barQ = barD + 8, barQok = barQ + 8;
  const uint32_t barFree = barQok + 8;
  volatile int* info = reinterpret_cast<volatile int*>(sm + kOffInfo);
  constexpr int kLastBatch = kNAtt - kHKV * kItemsPerPair;

  uint2 xr[9];
  if (warp < 4) {
    const uint2* xp = reinterpret_cast<const uint2*>(x + (warp * 2 + (lane >> 4)) * kD) + (lane & 15);
#pragma unroll
    for (int i = 0; i < 9; i++) xr[i] = __ldg(xp + i * 16);
  }
  if (warp == 5 && lane < 6)
    asm volatile("prefetch.tensormap [%0];" ::"l"(reinterpret_cast<const CUtensorMap*>(&maps) + lane) : "memory");
  unsigned nextDyn = 0;
  uint64_t pol = 0;
  if (warp < 4) {
    if (cta < kSliceCtas) {
      const uint32_t dst = sb + kOffW + warp * 9216 + (lane >> 2) * 64 + (((lane & 3) ^ ((lane >> 3) & 3)) << 4);
      const char* src = wqp + (size_t)(warp * 144 + (lane >> 2)) * 8192 + cta * 64 + (lane & 3) * 16;
#pragma unroll
      for (int i = 0; i < 18; i++) cp_async16(dst + i * 512, src + (size_t)i * 65536);
      asm volatile("cp.async.commit_group;" ::: "memory");
    }
  } else if (tid == 128) {
    TS(0);
    nextDyn = atom_add(&g_ctr.claim, 1);
#pragma unroll
    for (int i = 0; i < kNumBars; i++) {
      const int o = (i - 3 * kSlots) * 8;
      mbar_init(barFull + i * 8, (o == 0 || o == 8 || o == 40 || o == 48) ? 4 : 1);
    }
    asm volatile("fence.mbarrier_init.release.cluster;" ::: "memory");
    asm volatile("createpolicy.fractional.L2::evict_first.b64 %0, 1.0;" : "=l"(pol));
    TS(19);
#pragma unroll
    for (int w = 0; w < kSlots; w++) {
      info[w] = cta;
      mbar_arrive(barInfo + w * 8);
      mbar_expect_tx(barFull + w * 8, 9216);
      tma2d(sb + kOffRing + w * kSlotBytes, w < 4 ? &maps.wg : &maps.wu, cta * 32, (w & 3) * 144, barFull + w * 8, pol);
    }
  }
  __syncthreads();

  if (warp >= 4) {
  if (warp == 4) {
    if (lane == 0) {
      int item = cta, n = kSlots;
      while (true) {
        const int nsub = item < kNFfn ? 12 : 4;
#pragma unroll 1
        for (int w = item == cta ? kSlots : 0; w < nsub; w++, n++) {
          const int slot = n & (kSlots - 1);
          mbar_wait(barEmpty + slot * 8, ((n / kSlots) & 1) ^ 1);
          info[slot] = item;
          mbar_arrive(barInfo + slot * 8);
          const uint32_t fb = barFull + slot * 8;
          const uint32_t dst = sb + kOffRing + slot * kSlotBytes;
          if (item >= kNFfn) {
            if (item < kNItems) {
              mbar_expect_tx(fb, kSlotBytes);
              const int row = (item - kNFfn) * kItemRows + w * 32;
              tma3d(dst, &maps.k, 0, row, 0, fb, pol);
              tma3d(dst + 8192, &maps.v, 0, row, 0, fb, pol);
            }
          } else {
            mbar_expect_tx(fb, 9216);
            const int c = (w & 3) * 144;
            if (w < 8) tma2d(dst, w < 4 ? &maps.wg : &maps.wu, item * 32, c, fb, pol);
            else tma2d(dst, &maps.wd, c, item * 32, fb, pol);
          }
        }
        if (item >= kNItems) break;
        item = (int)nextDyn + G;
        if (item < kNItems) nextDyn = atom_add(&g_ctr.claim, 1);
      }
      if (cta < kSliceCtas) {
        mbar_wait(barFull + ((n - 5) & (kSlots - 1)) * 8, ((n - 5) / kSlots) & 1);
        mbar_expect_tx(barWo, 36864);
        tma4d(sb + kOffW, &maps.wo, 0, (cta & 7) * 16, (cta >> 3) * 2, 0, barWo, pol);
      }
      TS(3);
    }
  } else if (warp == 5) {
    const float* mb = reinterpret_cast<const float*>(sm + kOffMbuf);
    int pend = -1;
    int batch = 0;
    if (lane == 0) {
      if (cta < kSliceCtas) {
        mbar_wait(barQ, 0);
        red_release(&g_ctr.qready, 1);
        TS(10);
      }
      poll_ge(&g_ctr.qready, kSliceCtas, 50);
      mbar_arrive(barQok);
      TS(1);
    }
    __syncwarp();
    for (int kk = 0;; kk++) {
      const int buf = kk & 1;
      mbar_wait(barMfull + buf * 8, (kk >> 1) & 1);
      const float* p = mb + buf * 4 * kMbufStride;
      const int item = __float_as_int(p[260]);
      if (pend >= 0 && lane == 0) red_release(&g_ctr.done[pend * 32], 1);
      if (item < 0) break;
      if ((item >> 10) != batch) {
        batch = item >> 10;
        if (batch >= 2) mbar_wait(barFree + (batch - 2) * 8, 0);
      }
      float4 ml[4];
#pragma unroll
      for (int w = 0; w < 4; w++) ml[w] = *reinterpret_cast<const float4*>(p + w * kMbufStride + 256);
      const float M0 = fmaxf(fmaxf(ml[0].x, ml[1].x), fmaxf(ml[2].x, ml[3].x));
      const float M1 = fmaxf(fmaxf(ml[0].z, ml[1].z), fmaxf(ml[2].z, ml[3].z));
      float4 a = make_float4(0.f, 0.f, 0.f, 0.f), b = a;
      float L0 = 0.f, L1 = 0.f;
#pragma unroll
      for (int w = 0; w < 4; w++) {
        const float s0 = ex2(ml[w].x - M0), s1 = ex2(ml[w].z - M1);
        L0 = fmaf(s0, ml[w].y, L0);
        L1 = fmaf(s1, ml[w].w, L1);
        const float4 u = *reinterpret_cast<const float4*>(p + w * kMbufStride + lane * 4);
        const float4 v = *reinterpret_cast<const float4*>(p + w * kMbufStride + 128 + lane * 4);
        a.x = fmaf(s0, u.x, a.x); a.y = fmaf(s1, u.y, a.y); a.z = fmaf(s0, u.z, a.z); a.w = fmaf(s1, u.w, a.w);
        b.x = fmaf(s0, v.x, b.x); b.y = fmaf(s1, v.y, b.y); b.z = fmaf(s0, v.z, b.z); b.w = fmaf(s1, v.w, b.w);
      }
      float* dst = g_po + (size_t)PSLOT(item >> 6) * (kItemsPerPair * 256) + (item & 63) * 256;
      stx4(dst + lane * 4, a);
      stx4(dst + 128 + lane * 4, b);
      if (lane < 8)
        stx4(reinterpret_cast<float*>(g_pml + (PSLOT(item >> 6) * 8 + lane) * kItemsPerPair + (item & 63)), make_float4(M0, L0, M1, L1));
      __syncwarp();
      pend = item >> 6;
      if (lane == 0) mbar_arrive(barMempty + buf * 8);
      if (item >= kLastBatch) pend = -1;
    }
    if (lane == 0) { TS(4); }
  } else {
    const int cw = warp - 6;
    const int ci64 = tid - 192;
    mbar_wait(barQok, 0);
    if (ci64 == 0) {
      mbar_wait(barD, 0);
      red_release(&g_ctr.ddone, 1);
    }
    if (cta < kSliceCtas) {
      if (lane == 0) poll_ge(&g_ctr.ddone, G, 500);
      __syncwarp();
      float* ssum = reinterpret_cast<float*>(sm + kOffSsum);
      if (ci64 < 63) {
        const int q = ci64 % 9, pg = ci64 / 9;
        float4 acc = make_float4(0.f, 0.f, 0.f, 0.f);
#pragma unroll 4
        for (int p = pg; p < G; p += 7) {
          const float4 v = ldx4(g_dp + p * kOutElems + cta * 36 + q * 4);
          acc.x += v.x; acc.y += v.y; acc.z += v.z; acc.w += v.w;
        }
        *reinterpret_cast<float4*>(ssum + pg * 36 + q * 4) = acc;
      }
      float* g7 = reinterpret_cast<float*>(sm + kOffG7);
      if (cta < kRow7Ctas) {
        float acc = 0.f;
#pragma unroll 4
        for (int p = ci64 >> 3; p < G; p += 8) acc += __ldcg(g_dp + p * kOutElems + (cta * 8 + (ci64 & 7)) * 8 + 7);
        g7[ci64] = acc;
      }
      bar_sync(2, 64);
      if (cta < kRow7Ctas && ci64 >= 56) {
        float d = 0.f;
#pragma unroll
        for (int k = 0; k < 8; k++) d += g7[k * 8 + (ci64 & 7)];
        g7[64 + (ci64 & 7)] = bf16r(silu_f(bf16r(d)));
      }
      if (ci64 < 36) {
        float d = 0.f;
#pragma unroll
        for (int k = 0; k < 7; k++) d += ssum[k * 36 + ci64];
        ssum[252 + ci64] = bf16r(silu_f(bf16r(d)));
      }
      const int kvh = cta >> 3, sl = cta & 7;
      float2* wbuf = reinterpret_cast<float2*>(sm + kOffWbuf) + cw * 64;
      __nv_bfloat16* os = reinterpret_cast<__nv_bfloat16*>(sm + kOffOs);
      const int ci = lane >> 3, q4 = lane & 7;
#pragma unroll 1
      for (int b = cw; b < kB; b += 2) {
        const int pair = b * kHKV + kvh;
        if (b == 4 + cw) {
#pragma unroll 2
          for (int k = 0; k < 18; k++) clr4(g_sp + cta * kOutElems + (k * 64 + ci64) * 4);
          const int pair7 = PSLOT(7 * kHKV + kvh);
#pragma unroll 2
          for (int k = 0; k < 8; k++)
            clr4(g_po + ((size_t)pair7 * kItemsPerPair + k * 8 + (ci64 >> 3)) * 256 + sl * 32 + (ci64 & 7) * 4);
          clr4(reinterpret_cast<float*>(g_pml + (pair7 * 8 + sl) * kItemsPerPair + ci64));
          if (cta < kRow7Ctas) {
#pragma unroll
            for (int k = 0; k < 4; k++) clr4(g_s7 + cta * 1024 + (k * 64 + ci64) * 4);
          }
          __syncwarp();
          if (lane == 0) red_release(&g_ctr.zready, 1);
        }
        if (b >= 2 && lane == 0) {
          if (b == 7) poll_ge(&g_ctr.zready, kSliceCtas * 2, 200);
          else poll_ge(&g_ctr.cons[(b - 2) * 32], kSliceCtas, 200);
          mbar_arrive(barFree + (b - 2) * 8);
        }
        if (b == 7) break;
        const float* pml = reinterpret_cast<const float*>(g_pml + (PSLOT(pair) * 8 + sl) * kItemsPerPair);
        if (lane == 0) poll_ge(&g_ctr.done[pair * 32], kItemsPerPair, 300);
        __syncwarp();
        const float* po = g_po + (size_t)PSLOT(pair) * kItemsPerPair * 256 + sl * 32 + q4 * 4 + ci * 256;
        float4 v[18];
        gather18(v, po, pml + lane * 4);
        __syncwarp();
        if (lane == 0 && b < 5) red_release(&g_ctr.cons[b * 32], 1);
        const float4 mlA = v[16], mlB = v[17];
        const float M0 = warp_max(fmaxf(mlA.x, mlB.x)), M1 = warp_max(fmaxf(mlA.z, mlB.z));
        const float wA0 = ex2(mlA.x - M0), wA1 = ex2(mlA.z - M1), wB0 = ex2(mlB.x - M0), wB1 = ex2(mlB.z - M1);
        float L0 = wA0 * mlA.y + wB0 * mlB.y, L1 = wA1 * mlA.w + wB1 * mlB.w;
        wbuf[lane] = make_float2(wA0, wA1);
        wbuf[32 + lane] = make_float2(wB0, wB1);
        __syncwarp();
        float4 acc = make_float4(0.f, 0.f, 0.f, 0.f);
#pragma unroll
        for (int k = 0; k < 16; k++) {
          const float2 w2 = wbuf[k * 4 + ci];
          acc.x = fmaf(w2.x, v[k].x, acc.x); acc.y = fmaf(w2.y, v[k].y, acc.y);
          acc.z = fmaf(w2.x, v[k].z, acc.z); acc.w = fmaf(w2.y, v[k].w, acc.w);
        }
#pragma unroll
        for (int o = 1; o <= 16; o <<= 1) {
          L0 += __shfl_xor_sync(0xffffffffu, L0, o);
          L1 += __shfl_xor_sync(0xffffffffu, L1, o);
          if (o >= 8) {
            acc.x += __shfl_xor_sync(0xffffffffu, acc.x, o); acc.y += __shfl_xor_sync(0xffffffffu, acc.y, o);
            acc.z += __shfl_xor_sync(0xffffffffu, acc.z, o); acc.w += __shfl_xor_sync(0xffffffffu, acc.w, o);
          }
        }
        if (lane < 8) {
          const float r0 = 1.0f / L0, r1 = 1.0f / L1;
          *reinterpret_cast<uint32_t*>(os + b * 40 + q4 * 2) = pack_bf16(acc.x * r0, acc.z * r0);
          *reinterpret_cast<uint32_t*>(os + b * 40 + 16 + q4 * 2) = pack_bf16(acc.y * r1, acc.w * r1);
        }
        __syncwarp();
      }
      if (lane == 0) { TS(5 + cw); }
      __syncwarp();
      if (cta < kRow7Ctas) bar_arrive(4, 192);
    } else if (lane == 0) {
      for (int b = 2 + cw; b < kB; b += 2) {
        if (b == 7) poll_ge(&g_ctr.zready, kSliceCtas * 2, 500);
        else poll_ge(&g_ctr.cons[(b - 2) * 32], kSliceCtas, 500);
        mbar_arrive(barFree + (b - 2) * 8);
      }
    }
  }
    __syncwarp();
    if (cta < kSliceCtas) {
      const int aw = warp - 4, at = tid - 128;
      const int g = lane >> 2, t = lane & 3;
      const int oe = cta * 36 + at;
      float xv = 0.f;
      if (at < 36) xv = __bfloat162float(x[(oe & 7) * kD + (oe >> 3)]);
      mbar_wait(barFree + 5 * 8, 0);
      mbar_wait(barWo, 0);
      uint32_t a[18][4];
      load_wo(a, sb + kOffW, aw, lane);
      bar_sync(3, 128);
      uint32_t ob[4] = {0u, 0u, 0u, 0u};
      if (g < 7) {
        const __nv_bfloat16* os = reinterpret_cast<const __nv_bfloat16*>(sm + kOffOs) + g * 40 + t * 2;
#pragma unroll
        for (int j = 0; j < 4; j++) ob[j] = *reinterpret_cast<const uint32_t*>(os + j * 8);
      }
#pragma unroll
      for (int mt = 0; mt < 9; mt++) {
        float c[4] = {0.f, 0.f, 0.f, 0.f};
        mma16816(c, a[2 * mt], ob[0], ob[1]);
        mma16816(c, a[2 * mt + 1], ob[2], ob[3]);
#pragma unroll
        for (int h = 0; h < 2; h++) {
          const int e = ((mt * 2 + h) * 8 + g) * 8 + t * 2, u = e / 36;
          stx2(g_sp + ((aw * 32 + u) * kSliceCtas + cta) * 36 + (e - u * 36), c[2 * h], c[2 * h + 1]);
        }
      }
      if (lane == 0) { TS(40 + aw); }
      bar_sync(5, 256);
      const float* fp = g_sp + cta * kOutElems + at * 4;
      const int fcnt = at < 18 ? 10 : (at < 126 ? 9 : 0);
      float4 f[10];
#pragma unroll
      for (int k = 0; k < 10; k++) f[k] = k < fcnt ? ldx4(fp + k * 504) : make_float4(-0.f, -0.f, -0.f, -0.f);
      for (int it = 0;; it++) {
        bool ok = true;
#pragma unroll
        for (int k = 0; k < 10; k++) ok = ok && full4(f[k]);
        if (__all_sync(0xffffffffu, ok)) break;
        if (it > kSpinLimit) __trap();
        __nanosleep(40);
#pragma unroll
        for (int k = 0; k < 10; k++)
          if (!full4(f[k])) f[k] = ldx4(fp + k * 504);
      }
      float* fsum = reinterpret_cast<float*>(sm + kOffFsum);
      float4 acc = f[0];
#pragma unroll
      for (int k = 1; k < 10; k++) { acc.x += f[k].x; acc.y += f[k].y; acc.z += f[k].z; acc.w += f[k].w; }
      if (at < 126) *reinterpret_cast<float4*>(fsum + at * 4) = acc;
      bar_sync(3, 128);
      if (at < 36 && (oe & 7) != 7) {
        float s = 0.f;
#pragma unroll
        for (int k = 0; k < 14; k++) s += fsum[k * 36 + at];
        const float gt = reinterpret_cast<const float*>(sm + kOffSsum)[252 + at];
        out[(oe & 7) * kD + (oe >> 3)] = __float2bfloat16_rn(xv + bf16r(bf16r(s) * gt));
      }
      if (lane == 0) { TS(56 + aw); }
    }
  } else {
    const int g = lane >> 2, t = lane & 3;
    __nv_bfloat16* xn = reinterpret_cast<__nv_bfloat16*>(sm + kOffXn);
    {
      float v[36];
#pragma unroll
      for (int i = 0; i < 9; i++) {
        v[4 * i] = __uint_as_float(xr[i].x << 16);
        v[4 * i + 1] = __uint_as_float(xr[i].x & 0xffff0000u);
        v[4 * i + 2] = __uint_as_float(xr[i].y << 16);
        v[4 * i + 3] = __uint_as_float(xr[i].y & 0xffff0000u);
      }
      float s = 0.f;
#pragma unroll
      for (int i = 0; i < 36; i++) s += v[i];
#pragma unroll
      for (int o = 8; o > 0; o >>= 1) s += __shfl_xor_sync(0xffffffffu, s, o);
      const float mean = s * (1.0f / kD);
      float q = 0.f;
#pragma unroll
      for (int i = 0; i < 36; i++) { const float d = v[i] - mean; q = fmaf(d, d, q); }
#pragma unroll
      for (int o = 8; o > 0; o >>= 1) q += __shfl_xor_sync(0xffffffffu, q, o);
      const float mb = bf16r(mean);
      const float rden = 1.0f / bf16r(sqrtf(bf16r(bf16r(q * (1.0f / kD)) + 1e-5f)));
      __nv_bfloat16* xw = xn + (warp * 2 + (lane >> 4)) * kXnPitch + (lane & 15) * 4;
#pragma unroll
      for (int i = 0; i < 9; i++)
        *reinterpret_cast<uint2*>(xw + i * 64) =
            make_uint2(pack_bf16(bf16r(v[4 * i] - mb) * rden, bf16r(v[4 * i + 1] - mb) * rden),
                       pack_bf16(bf16r(v[4 * i + 2] - mb) * rden, bf16r(v[4 * i + 3] - mb) * rden));
    }
    bar_sync(1, 128);
    if (tid == 0) { TS(18); }
    float* mb = reinterpret_cast<float*>(sm + kOffMbuf);
    const uint32_t r8 = lane & 7;
    const uint32_t guLane = (r8 + (lane >> 4) * 8) * 64 + ((((lane >> 3) & 1) ^ (r8 >> 1)) << 4);
    int slot = warp, item;
    uint32_t fph = 0;
    {
      uint32_t xb[9][2];
#pragma unroll
      for (int ks = 0; ks < 9; ks++) {
        xb[ks][0] = *reinterpret_cast<const uint32_t*>(xn + g * kXnPitch + warp * 144 + ks * 16 + t * 2);
        xb[ks][1] = *reinterpret_cast<const uint32_t*>(xn + g * kXnPitch + warp * 144 + ks * 16 + 8 + t * 2);
      }
      if (cta < kSliceCtas) {
        if (tid == 0) {
          g_ctr.done[cta * 32] = 0;
          if (cta < 8) g_ctr.cons[cta * 32] = 0;
          if (cta == 0) { g_ctr.ddone = 0; g_ctr.zready = 0; g_ctr.exitc = 0; }
        }
        asm volatile("cp.async.wait_group 0;" ::: "memory");
        __syncwarp();
        if (tid == 0) { TS(9); }
        const uint32_t lo = sb + kOffW + warp * 9216;
        uint32_t a[18][4];
#pragma unroll
        for (int i = 0; i < 18; i++) ldsm4t(a[i], lo + (guLane ^ ((i & 1) * 32)) + (i >> 1) * 1024);
        float c[2][4] = {{0.f, 0.f, 0.f, 0.f}, {0.f, 0.f, 0.f, 0.f}};
#pragma unroll
        for (int i = 0; i < 18; i++) mma16816(c[i & 1], a[i], xb[i >> 1][0], xb[i >> 1][1]);
        float* qr = mb + warp * 256;
#pragma unroll
        for (int mt = 0; mt < 2; mt++) {
          *reinterpret_cast<float2*>(qr + (mt * 16 + g) * 8 + t * 2) = make_float2(c[mt][0], c[mt][1]);
          *reinterpret_cast<float2*>(qr + (mt * 16 + 8 + g) * 8 + t * 2) = make_float2(c[mt][2], c[mt][3]);
        }
        bar_sync(1, 128);
        const int b = tid >> 4, cp = tid & 15;
        float q0 = 0.f, q1 = 0.f;
#pragma unroll
        for (int w = 0; w < 4; w++) {
          q0 += mb[w * 256 + (cp * 2) * 8 + b];
          q1 += mb[w * 256 + (cp * 2 + 1) * 8 + b];
        }
        const int col = cta * 32 + cp * 2;
        const int head = col >> 7, d = col & 127;
        const int pos = (head & 1) * 128 + (d >> 5) * 32 + ((d & 7) >> 1) * 8 + ((d >> 4) & 1) * 4 + ((d >> 3) & 1) * 2;
        *reinterpret_cast<uint32_t*>(g_q + (b * kHKV + (head >> 1)) * 256 + pos) = pack_bf16(q0, q1);
        __syncwarp();
        if (lane == 0) mbar_arrive(barQ);
        if (tid == 32) { TS(17); }
      } else {
        bar_sync(1, 128);
      }

      float dacc[9][4];
#pragma unroll
      for (int i = 0; i < 9; i++) dacc[i][0] = dacc[i][1] = dacc[i][2] = dacc[i][3] = 0.f;
      float* red = reinterpret_cast<float*>(sm + kOffXn);
      const uint32_t dnLane = (r8 + (lane >> 4) * 8) * 288 + ((lane >> 3) & 1) * 16;
      while (true) {
        mbar_wait(barInfo + slot * 8, fph);
        item = info[slot];
        if (item >= kNFfn) break;
        uint32_t a[18][4];
        float* rw = red + warp * 512;
#pragma unroll 1
        for (int gu = 0; gu < 2; gu++) {
          mbar_wait(barFull + slot * 8, fph);
          if (tid == 96 && item == cta) { TS(15 + gu); }
          const uint32_t base = sb + kOffRing + slot * kSlotBytes;
#pragma unroll
          for (int i = 0; i < 18; i++) ldsm4t(a[i], base + (guLane ^ ((i & 1) * 32)) + (i >> 1) * 1024);
          float c[2][4] = {{0.f, 0.f, 0.f, 0.f}, {0.f, 0.f, 0.f, 0.f}};
#pragma unroll
          for (int i = 0; i < 18; i++) mma16816(c[i & 1], a[i], xb[i >> 1][0], xb[i >> 1][1]);
#pragma unroll
          for (int mt = 0; mt < 2; mt++) {
            float* r = rw + gu * 256 + (2 * t) * 32 + mt * 16 + g;
            r[0] = c[mt][0]; r[32] = c[mt][1]; r[8] = c[mt][2]; r[40] = c[mt][3];
          }
          __syncwarp();
          if (lane == 0) mbar_arrive(barEmpty + slot * 8);
          slot += 4;
          if (slot >= kSlots) { slot -= kSlots; fph ^= 1; }
        }
        bar_sync(1, 128);
        uint32_t hb[4];
#pragma unroll
        for (int j = 0; j < 4; j++) {
          float2 gs = make_float2(0.f, 0.f), us = gs;
#pragma unroll
          for (int w = 0; w < 4; w++) {
            const float* rr = red + w * 512 + g * 32 + j * 8 + t * 2;
            const float2 a2 = *reinterpret_cast<const float2*>(rr), b2 = *reinterpret_cast<const float2*>(rr + 256);
            gs.x += a2.x; gs.y += a2.y; us.x += b2.x; us.y += b2.y;
          }
          hb[j] = pack_bf16(bf16r(silu_f(bf16r(gs.x))) * bf16r(us.x), bf16r(silu_f(bf16r(gs.y))) * bf16r(us.y));
        }
        mbar_wait(barFull + slot * 8, fph);
        if (tid == 96 && item == cta) { TS(30); }
        const uint32_t base = sb + kOffRing + slot * kSlotBytes + dnLane;
#pragma unroll
        for (int i = 0; i < 18; i++) ldsm4t(a[i], base + (i >> 1) * 32 + (i & 1) * 4608);
#pragma unroll
        for (int i = 0; i < 18; i++) mma16816(dacc[i >> 1], a[i], hb[(i & 1) * 2], hb[(i & 1) * 2 + 1]);
        bar_sync(1, 128);
        if (lane == 0) mbar_arrive(barEmpty + slot * 8);
        slot += 4;
        if (slot >= kSlots) { slot -= kSlots; fph ^= 1; }
      }
      if (tid == 0) { TS(12); }
      float* dp = g_dp + cta * kOutElems + (warp * 144 + g) * 8 + t * 2;
#pragma unroll
      for (int mt = 0; mt < 9; mt++) {
        *reinterpret_cast<float2*>(dp + mt * 128) = make_float2(dacc[mt][0], dacc[mt][1]);
        *reinterpret_cast<float2*>(dp + mt * 128 + 64) = make_float2(dacc[mt][2], dacc[mt][3]);
      }
      __syncwarp();
      if (lane == 0) mbar_arrive(barD);
      mbar_wait(barQok, 0);
      if (tid == 0) { TS(2); }
    }

    const float kScale = 0.08838834764831845f * 1.4426950408889634f;
    const uint32_t kLane = (r8 + ((lane >> 3) & 1) * 8) * 128 + (((lane >> 4) ^ r8) << 4);
    const uint32_t vLane = 8192 + (r8 + (lane >> 4) * 8) * 128 + ((((lane >> 3) & 1) ^ r8) << 4);
    int kk = 0;
    while (item < kNItems) {
      item -= kNFfn;
      uint4 qv[4];
      if (g < 2) {
        const uint4* qs = reinterpret_cast<const uint4*>(g_q + (item >> 6) * 256 + g * 128 + t * 8);
#pragma unroll
        for (int i = 0; i < 4; i++) qv[i] = qs[i * 4];
      } else {
#pragma unroll
        for (int i = 0; i < 4; i++) qv[i] = make_uint4(0u, 0u, 0u, 0u);
      }
      mbar_wait(barFull + slot * 8, fph);
      const uint32_t base = sb + kOffRing + slot * kSlotBytes;
      uint32_t ka[16][4], va[16][4];
#pragma unroll
      for (int i = 0; i < 16; i++)
        ldsm4(ka[i], base + ((kLane ^ (((i >> 1) & 3) << 5)) + (i >> 3) * 4096 + (i & 1) * 2048));
#pragma unroll
      for (int i = 0; i < 16; i++)
        ldsm4t(va[i], base + ((vLane ^ (((i >> 1) & 3) << 5)) + (i >> 3) * 4096 + (i & 1) * 2048));
      float s[2][4], s2[2][4];
#pragma unroll
      for (int i = 0; i < 4; i++) s[0][i] = s[1][i] = s2[0][i] = s2[1][i] = 0.f;
#pragma unroll
      for (int kp = 0; kp < 4; kp++) {
        mma16816(s[0], ka[4 * kp], qv[kp].x, qv[kp].y);
        mma16816(s[1], ka[4 * kp + 1], qv[kp].x, qv[kp].y);
        mma16816(s2[0], ka[4 * kp + 2], qv[kp].z, qv[kp].w);
        mma16816(s2[1], ka[4 * kp + 3], qv[kp].z, qv[kp].w);
      }
#pragma unroll
      for (int i = 0; i < 4; i++) { s[0][i] += s2[0][i]; s[1][i] += s2[1][i]; }
      float m0 = fmaxf(fmaxf(s[0][0], s[0][2]), fmaxf(s[1][0], s[1][2]));
      float m1 = fmaxf(fmaxf(s[0][1], s[0][3]), fmaxf(s[1][1], s[1][3]));
#pragma unroll
      for (int o = 4; o <= 16; o <<= 1) {
        m0 = fmaxf(m0, __shfl_xor_sync(0xffffffffu, m0, o));
        m1 = fmaxf(m1, __shfl_xor_sync(0xffffffffu, m1, o));
      }
      m0 *= kScale; m1 *= kScale;
      float l0 = 0.f, l1 = 0.f;
      uint32_t pb[2][2];
#pragma unroll
      for (int mt = 0; mt < 2; mt++) {
        const float p0 = ex2(fmaf(s[mt][0], kScale, -m0)), p1 = ex2(fmaf(s[mt][1], kScale, -m1));
        const float p2 = ex2(fmaf(s[mt][2], kScale, -m0)), p3 = ex2(fmaf(s[mt][3], kScale, -m1));
        l0 += p0 + p2; l1 += p1 + p3;
        pb[mt][0] = movmat(pack_bf16(p0, p1));
        pb[mt][1] = movmat(pack_bf16(p2, p3));
      }
      float o_[8][4];
#pragma unroll
      for (int j = 0; j < 8; j++) {
        o_[j][0] = o_[j][1] = o_[j][2] = o_[j][3] = 0.f;
        mma16816(o_[j], va[2 * j], pb[0][0], pb[0][1]);
      }
#pragma unroll
      for (int j = 0; j < 8; j++) mma16816(o_[j], va[2 * j + 1], pb[1][0], pb[1][1]);
#pragma unroll
      for (int o = 4; o <= 16; o <<= 1) {
        l0 += __shfl_xor_sync(0xffffffffu, l0, o);
        l1 += __shfl_xor_sync(0xffffffffu, l1, o);
      }
      const int buf = kk & 1;
      mbar_wait(barMempty + buf * 8, ((kk >> 1) & 1) ^ 1);
      float* p = mb + (buf * 4 + warp) * kMbufStride;
      if (t == 0) {
#pragma unroll
        for (int j = 0; j < 8; j++) {
          *reinterpret_cast<float2*>(p + (j * 16 + g) * 2) = make_float2(o_[j][0], o_[j][1]);
          *reinterpret_cast<float2*>(p + (j * 16 + 8 + g) * 2) = make_float2(o_[j][2], o_[j][3]);
        }
        if (g == 0) {
          *reinterpret_cast<float4*>(p + 256) = make_float4(m0, l0, m1, l1);
          p[260] = __int_as_float(item);
        }
      }
      __syncwarp();
      if (lane == 0) {
        mbar_arrive(barMfull + buf * 8);
        mbar_arrive(barEmpty + slot * 8);
      }
      kk++;
      slot += 4;
      if (slot >= kSlots) { slot -= kSlots; fph ^= 1; }
      mbar_wait(barInfo + slot * 8, fph);
      item = info[slot];
    }
    {
      const int buf = kk & 1;
      mbar_wait(barMempty + buf * 8, ((kk >> 1) & 1) ^ 1);
      if (lane == 0) {
        mb[(buf * 4 + warp) * kMbufStride + 260] = __int_as_float(-1);
        mbar_arrive(barMfull + buf * 8);
        if (warp == 0) red_relaxed(&g_ctr.exitc, 1);
      }
      __syncwarp();
    }
    if (tid == 0) { TS(11); }
    if (lane == 0) { TS(32 + warp); }
    if (cta < kSliceCtas) {
      float xv = 0.f;
      if (tid < 8 && cta < kRow7Ctas) xv = __bfloat162float(x[7 * kD + cta * 8 + tid]);
      mbar_wait(barFree + 5 * 8, 0);
      const int ps = PSLOT(7 * kHKV + (cta >> 3)), sl = cta & 7;
      const int ci = lane >> 3, q4 = lane & 7;
      const float* po = g_po + (ps * kItemsPerPair + warp * 16 + ci) * 256 + sl * 32 + q4 * 4;
      const float* pml = reinterpret_cast<const float*>(g_pml + (ps * 8 + sl) * kItemsPerPair + warp * 16 + (lane & 15));
      float4 v[5];
#pragma unroll
      for (int k = 0; k < 5; k++) v[k] = ldx4(k < 4 ? po + k * 1024 : pml);
      uint32_t a[18][4], ob[4];
      bool haveWo = false;
      for (int it = 0;; it++) {
        if (!haveWo && __all_sync(0xffffffffu, mbar_test(barWo, 0))) {
          load_wo(a, sb + kOffW, warp, lane);
          haveWo = true;
        }
        bool ok = true;
#pragma unroll
        for (int k = 0; k < 5; k++) ok = ok && full4(v[k]);
        if (__all_sync(0xffffffffu, ok) && haveWo) break;
        if (it > kSpinLimit) __trap();
#pragma unroll
        for (int k = 0; k < 5; k++)
          if (!full4(v[k])) v[k] = ldx4(k < 4 ? po + k * 1024 : pml);
      }
      if (lane == 0) { TS(36 + warp); }
      float* cb = reinterpret_cast<float*>(sm + kOffCbuf);
      {
        const float M0 = warp_max(v[4].x), M1 = warp_max(v[4].z);
        const float w0 = ex2(v[4].x - M0), w1 = ex2(v[4].z - M1);
        float L0 = w0 * v[4].y, L1 = w1 * v[4].w;
        float4 acc = make_float4(0.f, 0.f, 0.f, 0.f);
#pragma unroll
        for (int k = 0; k < 4; k++) {
          const float a0 = __shfl_sync(0xffffffffu, w0, k * 4 + ci), a1 = __shfl_sync(0xffffffffu, w1, k * 4 + ci);
          acc.x = fmaf(a0, v[k].x, acc.x); acc.y = fmaf(a1, v[k].y, acc.y);
          acc.z = fmaf(a0, v[k].z, acc.z); acc.w = fmaf(a1, v[k].w, acc.w);
        }
#pragma unroll
        for (int o = 1; o <= 16; o <<= 1) {
          if (o <= 8) {
            L0 += __shfl_xor_sync(0xffffffffu, L0, o);
            L1 += __shfl_xor_sync(0xffffffffu, L1, o);
          }
          if (o >= 8) {
            acc.x += __shfl_xor_sync(0xffffffffu, acc.x, o); acc.y += __shfl_xor_sync(0xffffffffu, acc.y, o);
            acc.z += __shfl_xor_sync(0xffffffffu, acc.z, o); acc.w += __shfl_xor_sync(0xffffffffu, acc.w, o);
          }
        }
        if (lane < 8) {
          *reinterpret_cast<float2*>(cb + warp * 40 + q4 * 2) = make_float2(acc.x, acc.z);
          *reinterpret_cast<float2*>(cb + warp * 40 + 16 + q4 * 2) = make_float2(acc.y, acc.w);
          if (lane == 0) *reinterpret_cast<float4*>(cb + warp * 40 + 32) = make_float4(M0, L0, M1, L1);
        }
      }
      if (tid == 0) { TS(29); }
      bar_sync(1, 128);
      {
        float4 ml[4];
#pragma unroll
        for (int w = 0; w < 4; w++) ml[w] = *reinterpret_cast<const float4*>(cb + w * 40 + 32);
        const float M0 = fmaxf(fmaxf(ml[0].x, ml[1].x), fmaxf(ml[2].x, ml[3].x));
        const float M1 = fmaxf(fmaxf(ml[0].z, ml[1].z), fmaxf(ml[2].z, ml[3].z));
        float L0 = 0.f, L1 = 0.f;
        float2 o2[4] = {{0.f, 0.f}, {0.f, 0.f}, {0.f, 0.f}, {0.f, 0.f}};
#pragma unroll
        for (int w = 0; w < 4; w++) {
          const float s0 = ex2(ml[w].x - M0), s1 = ex2(ml[w].z - M1);
          L0 = fmaf(s0, ml[w].y, L0);
          L1 = fmaf(s1, ml[w].w, L1);
#pragma unroll
          for (int j = 0; j < 4; j++) {
            const float2 u = *reinterpret_cast<const float2*>(cb + w * 40 + j * 8 + t * 2);
            o2[j].x = fmaf(j < 2 ? s0 : s1, u.x, o2[j].x);
            o2[j].y = fmaf(j < 2 ? s0 : s1, u.y, o2[j].y);
          }
        }
        const float r0 = __frcp_rn(L0), r1 = __frcp_rn(L1);
#pragma unroll
        for (int j = 0; j < 4; j++) ob[j] = pack_bf16(o2[j].x * (j < 2 ? r0 : r1), o2[j].y * (j < 2 ? r0 : r1));
      }
      if (lane == 0) { TS(52 + warp); }
      {
        float c[10][4];
#pragma unroll
        for (int mt = 0; mt < 9; mt++) {
          c[mt][0] = c[mt][1] = c[mt][2] = c[mt][3] = 0.f;
          mma16816(c[mt], a[2 * mt], ob[0], ob[1]);
          mma16816(c[mt], a[2 * mt + 1], ob[2], ob[3]);
        }
        c[9][0] = c[9][2] = 0.f;
        float* s7 = g_s7 + ((warp * 18 + t) * kSliceCtas + cta) * 8 + g;
#pragma unroll
        for (int k = 0; k < 5; k++) {
          const float lo = (t & 1) ? c[2 * k][2] : c[2 * k][0], hi = (t & 1) ? c[2 * k + 1][2] : c[2 * k + 1][0];
          if (k < 4 || t < 2) stx1(s7 + k * 4 * kSliceCtas * 8, (t & 2) ? hi : lo);
        }
      }
      bar_arrive(5, 256);
      if (lane == 0) { TS(44 + warp); }
      if (tid == 0) { TS(7); TS(8); }
      if (cta < kRow7Ctas) {
        const float* hp = g_s7 + cta * 1024 + tid * 4;
        float4 f0 = ldx4(hp), f1 = ldx4(hp + 512);
        for (int it = 0; !__all_sync(0xffffffffu, full4(f0) && full4(f1)); it++) {
          if (it > kSpinLimit) __trap();
          if (!full4(f0)) f0 = ldx4(hp);
          if (!full4(f1)) f1 = ldx4(hp + 512);
        }
        if (lane == 0) { TS(48 + warp); }
        float* g7 = reinterpret_cast<float*>(sm + kOffG7);
        float4 h = make_float4(f0.x + f1.x, f0.y + f1.y, f0.z + f1.z, f0.w + f1.w);
#pragma unroll
        for (int o = 2; o <= 16; o <<= 1) {
          h.x += __shfl_xor_sync(0xffffffffu, h.x, o); h.y += __shfl_xor_sync(0xffffffffu, h.y, o);
          h.z += __shfl_xor_sync(0xffffffffu, h.z, o); h.w += __shfl_xor_sync(0xffffffffu, h.w, o);
        }
        if (lane < 2) *reinterpret_cast<float4*>(g7 + 72 + warp * 8 + lane * 4) = h;
        bar_sync(4, 192);
        if (tid < 8) {
          const float s = (g7[72 + tid] + g7[80 + tid]) + (g7[88 + tid] + g7[96 + tid]);
          out[7 * kD + cta * 8 + tid] = __float2bfloat16_rn(xv + bf16r(bf16r(s) * g7[64 + tid]));
        }
      }
      if (cta == 0 && tid == 96) {
        poll_ge(&g_ctr.exitc, G, 20);
        g_ctr.claim = 0;
        g_ctr.qready = 0;
      }
    }
    if (tid == 0) { TS(14); }
  }
}

__global__ void fb_ln(const __nv_bfloat16* x, float* xn) {
  const int lane = threadIdx.x;
  const __nv_bfloat16* xr = x + blockIdx.x * kD;
  float s = 0.f, q = 0.f;
  for (int i = lane; i < kD; i += 32) s += __bfloat162float(xr[i]);
  for (int o = 16; o > 0; o >>= 1) s += __shfl_xor_sync(0xffffffffu, s, o);
  const float mean = s * (1.0f / kD);
  for (int i = lane; i < kD; i += 32) { const float d = __bfloat162float(xr[i]) - mean; q = fmaf(d, d, q); }
  for (int o = 16; o > 0; o >>= 1) q += __shfl_xor_sync(0xffffffffu, q, o);
  const float den = bf16r(sqrtf(bf16r(bf16r(q * (1.0f / kD)) + 1e-5f)));
  for (int i = lane; i < kD; i += 32) xn[blockIdx.x * kD + i] = bf16r(bf16r(__bfloat162float(xr[i]) - bf16r(mean)) / den);
}
__global__ void fb_gemv(const float* a, const float* a2, const __nv_bfloat16* w, float* o, int K, int N) {
  const int n = blockIdx.x * 64 + threadIdx.x, b = blockIdx.y;
  float s = 0.f;
  for (int k = 0; k < K; k++) {
    const float v = a2 ? bf16r(bf16r(silu_f(a[b * K + k])) * a2[b * K + k]) : a[b * K + k];
    s = fmaf(v, __bfloat162float(w[(size_t)k * N + n]), s);
  }
  o[b * N + n] = bf16r(s);
}
__global__ void fb_att(const float* q, const __nv_bfloat16* kc, const __nv_bfloat16* vc, float* o) {
  __shared__ float sm_[8][132];
  const int warp = threadIdx.x >> 5, lane = threadIdx.x & 31;
  const size_t base = (size_t)(blockIdx.x >> 1) * kSK * 128 + lane * 4;
  float qv[4], acc[4] = {0.f, 0.f, 0.f, 0.f}, m = -INFINITY, l = 0.f;
  for (int i = 0; i < 4; i++) qv[i] = q[blockIdx.x * 128 + lane * 4 + i];
  for (int j = warp; j < kSK; j += 8) {
    float s = 0.f;
    for (int i = 0; i < 4; i++) s = fmaf(qv[i], __bfloat162float(kc[base + (size_t)j * 128 + i]), s);
    for (int x = 16; x > 0; x >>= 1) s += __shfl_xor_sync(0xffffffffu, s, x);
    s *= 0.08838834764831845f;
    const float mn = fmaxf(m, s), c = __expf(m - mn), pr = __expf(s - mn);
    l = l * c + pr;
    for (int i = 0; i < 4; i++) acc[i] = acc[i] * c + pr * __bfloat162float(vc[base + (size_t)j * 128 + i]);
    m = mn;
  }
  for (int i = 0; i < 4; i++) sm_[warp][lane * 4 + i] = acc[i];
  if (lane == 0) { sm_[warp][128] = m; sm_[warp][129] = l; }
  __syncthreads();
  if (threadIdx.x < 128) {
    float M = -INFINITY, L = 0.f, r = 0.f;
    for (int w = 0; w < 8; w++) M = fmaxf(M, sm_[w][128]);
    for (int w = 0; w < 8; w++) { const float c = __expf(sm_[w][128] - M); L += c * sm_[w][129]; r += c * sm_[w][threadIdx.x]; }
    o[blockIdx.x * 128 + threadIdx.x] = bf16r(r / L);
  }
}
__global__ void fb_out(const __nv_bfloat16* x, const float* s, const float* d, __nv_bfloat16* out) {
  const int i = blockIdx.x * 64 + threadIdx.x;
  out[i] = __float2bfloat16_rn(__bfloat162float(x[i]) + bf16r(s[i] * bf16r(silu_f(d[i]))));
}

typedef CUresult (*EncodeFn)(CUtensorMap*, CUtensorMapDataType, cuuint32_t, void*, const cuuint64_t*,
                             const cuuint64_t*, const cuuint32_t*, const cuuint32_t*, CUtensorMapInterleave,
                             CUtensorMapSwizzle, CUtensorMapL2promotion, CUtensorMapFloatOOBfill);

void encode(EncodeFn fn, CUtensorMap* m, const void* base, int rank, const cuuint64_t* dims, const cuuint64_t* strides,
            const cuuint32_t* box, CUtensorMapSwizzle sw,
            CUtensorMapL2promotion promo = CU_TENSOR_MAP_L2_PROMOTION_L2_128B) {
  const cuuint32_t es[4] = {1, 1, 1, 1};
  fn(m, CU_TENSOR_MAP_DATA_TYPE_BFLOAT16, rank, const_cast<void*>(base), dims, strides, box, es,
     CU_TENSOR_MAP_INTERLEAVE_NONE, sw, promo, CU_TENSOR_MAP_FLOAT_OOB_FILL_NONE);
}

}

extern "C" void kernel_launch(void* const* d_in, const int* in_sizes, int n_in, void* d_out, int out_size) {
  (void)in_sizes; (void)n_in; (void)out_size;
  static EncodeFn fn = nullptr;
  static int sms = 0;
  if (!sms) {
    void* p = nullptr;
    cudaDriverEntryPointQueryResult qr;
    cudaGetDriverEntryPoint("cuTensorMapEncodeTiled", &p, cudaEnableDefault, &qr);
    fn = (EncodeFn)p;
    int dev = 0;
    cudaGetDevice(&dev);
    cudaDeviceGetAttribute(&sms, cudaDevAttrMultiProcessorCount, dev);
    cudaFuncSetAttribute(fused_decode_kernel, cudaFuncAttributeMaxDynamicSharedMemorySize, kSmemBytes);
  }
  if (sms < kSliceCtas || !fn) {
    typedef const __nv_bfloat16* P;
    float* t = nullptr;
    cudaGetSymbolAddress((void**)&t, g_po);
    float *xn = t, *q = t + 8192, *o = q + 32768, *g = o + 32768, *u = g + 36864, *sv = u + 36864, *d = sv + 8192;
    fb_ln<<<kB, 32>>>((P)d_in[0], xn);
    fb_gemv<<<dim3(64, kB), 64>>>(xn, nullptr, (P)d_in[3], q, kD, 4096);
    fb_att<<<256, 256>>>(q, (P)d_in[1], (P)d_in[2], o);
    fb_gemv<<<dim3(9, kB), 64>>>(o, nullptr, (P)d_in[4], sv, 4096, kD);
    fb_gemv<<<dim3(72, kB), 64>>>(xn, nullptr, (P)d_in[6], g, kD, kF);
    fb_gemv<<<dim3(72, kB), 64>>>(xn, nullptr, (P)d_in[7], u, kD, kF);
    fb_gemv<<<dim3(9, kB), 64>>>(g, u, (P)d_in[8], d, kF, kD);
    fb_out<<<72, 64>>>((P)d_in[0], sv, d, (__nv_bfloat16*)d_out);
    return;
  }
  Maps maps;
  {
    const cuuint64_t dims[3] = {64, (cuuint64_t)kPairs * kSK, 2}, str[2] = {256, 128};
    const cuuint32_t box[3] = {64, 32, 2};
    encode(fn, &maps.k, d_in[1], 3, dims, str, box, CU_TENSOR_MAP_SWIZZLE_128B, CU_TENSOR_MAP_L2_PROMOTION_L2_256B);
    encode(fn, &maps.v, d_in[2], 3, dims, str, box, CU_TENSOR_MAP_SWIZZLE_128B, CU_TENSOR_MAP_L2_PROMOTION_L2_256B);
  }
  {
    const cuuint64_t dims[4] = {64, 128, 32, 9}, str[3] = {kD * 2, 128 * kD * 2, 128};
    const cuuint32_t box[4] = {64, 16, 2, 9};
    encode(fn, &maps.wo, d_in[4], 4, dims, str, box, CU_TENSOR_MAP_SWIZZLE_128B);
  }
  {
    const cuuint64_t dims[2] = {kF, kD}, str[1] = {kF * 2};
    const cuuint32_t box[2] = {32, 144};
    encode(fn, &maps.wg, d_in[6], 2, dims, str, box, CU_TENSOR_MAP_SWIZZLE_64B);
    encode(fn, &maps.wu, d_in[7], 2, dims, str, box, CU_TENSOR_MAP_SWIZZLE_64B);
  }
  {
    const cuuint64_t dims[2] = {kD, kF}, str[1] = {kD * 2};
    const cuuint32_t box[2] = {144, 32};
    encode(fn, &maps.wd, d_in[8], 2, dims, str, box, CU_TENSOR_MAP_SWIZZLE_NONE);
  }
  int grid = sms < kMaxCtas ? sms : kMaxCtas;
  fused_decode_kernel<<<grid, kThreads, kSmemBytes>>>(maps, (const __nv_bfloat16*)d_in[0], (const char*)d_in[3],
                                                      (__nv_bfloat16*)d_out);
}
```

```cpp
#include <cuda_runtime.h>
#include <cuda_bf16.h>
#include <cuda.h>
#include <stdint.h>

namespace {

constexpr int kB = 8, kD = 576, kHKV = 16, kSK = 8192, kF = 4608;
constexpr int kPairs = kB * kHKV;
constexpr int kItemRows = 128;
constexpr int kItemsPerPair = kSK / kItemRows;
constexpr int kNAtt = kPairs * kItemsPerPair;
constexpr int kNFfn = kF / 32;
constexpr int kNItems = kNAtt + kNFfn;
constexpr int kSlots = 8;
constexpr int kSlotBytes = 16384;
constexpr int kMaxCtas = kNFfn;
constexpr int kSliceCtas = 128;
constexpr int kRow7Ctas = 72;
constexpr int kThreads = 256;
constexpr int kOutElems = kB * kD;

constexpr int kOffRing = 0;
constexpr int kOffW = kOffRing + kSlots * kSlotBytes;
constexpr int kOffXn = kOffW + 36864;
constexpr int kXnPitch = 584;
constexpr int kOffMbuf = kOffXn + kB * kXnPitch * 2;
constexpr int kMbufStride = 264;
constexpr int kOffOs = kOffMbuf + 2 * 4 * kMbufStride * 4;
constexpr int kOffWbuf = kOffOs + 8 * 40 * 2;
constexpr int kOffFsum = kOffWbuf + 2 * 64 * 8;
constexpr int kOffSsum = kOffFsum + 14 * 36 * 4;
constexpr int kOffG7 = kOffSsum + 8 * 36 * 4;
constexpr int kOffCbuf = kOffG7 + 104 * 4;
constexpr int kOffInfo = kOffCbuf + 4 * 40 * 4;
constexpr int kOffBar = kOffInfo + 64;
constexpr int kNumBars = 3 * kSlots + 8 + 6;
constexpr int kSmemBytes = kOffBar + kNumBars * 8 + 1024;
static_assert(kSmemBytes <= 232448, "smem");

constexpr int kPartSlots = 48;
__device__ __forceinline__ int PSLOT(int pair) { return pair >= 112 ? pair - 80 : (pair & 31); }

struct Counters {
  unsigned claim;
  unsigned qready; unsigned pad1[30];
  unsigned ddone;  unsigned pad2[31];
  unsigned zready; unsigned pad3[31];
  unsigned exitc;  unsigned pad4[31];
  unsigned cons[8 * 32];
  unsigned done[kPairs * 32];
};

__device__ __align__(128) Counters g_ctr;
__device__ __align__(128) __nv_bfloat16 g_q[kPairs * 256];
__device__ __align__(128) float g_po[kPartSlots * kItemsPerPair * 256];
__device__ __align__(128) float4 g_pml[kPartSlots * 8 * kItemsPerPair];
__device__ __align__(128) float g_sp[kSliceCtas * kOutElems];
__device__ __align__(128) float g_s7[kRow7Ctas * kSliceCtas * 8];
__device__ __align__(128) float g_dp[kMaxCtas * kOutElems];

constexpr int kSpinLimit = 1 << 21;

__device__ __forceinline__ uint32_t smem_u32(const void* p) { return (uint32_t)__cvta_generic_to_shared(p); }
__device__ __forceinline__ void mbar_init(uint32_t bar, uint32_t cnt) {
  asm volatile("mbarrier.init.shared::cta.b64 [%0], %1;" ::"r"(bar), "r"(cnt) : "memory");
}
__device__ __forceinline__ void mbar_expect_tx(uint32_t bar, uint32_t bytes) {
  asm volatile("mbarrier.arrive.expect_tx.shared::cta.b64 _, [%0], %1;" ::"r"(bar), "r"(bytes) : "memory");
}
__device__ __forceinline__ void mbar_arrive(uint32_t bar) {
  asm volatile("mbarrier.arrive.shared::cta.b64 _, [%0];" ::"r"(bar) : "memory");
}
__device__ __forceinline__ void mbar_wait(uint32_t bar, uint32_t parity) {
  uint32_t done;
  int it = 0;
  do {
    asm volatile(
        "{\n.reg .pred p;\nmbarrier.try_wait.parity.shared::cta.b64 p, [%1], %2;\nselp.u32 %0, 1, 0, p;\n}"
        : "=r"(done) : "r"(bar), "r"(parity) : "memory");
    if (++it > kSpinLimit) __trap();
  } while (!done);
}
__device__ __forceinline__ bool mbar_test(uint32_t bar, uint32_t parity) {
  uint32_t done;
  asm volatile(
      "{\n.reg .pred p;\nmbarrier.test_wait.parity.shared::cta.b64 p, [%1], %2;\nselp.u32 %0, 1, 0, p;\n}"
      : "=r"(done) : "r"(bar), "r"(parity) : "memory");
  return done != 0;
}
__device__ __forceinline__ void tma2d(uint32_t dst, const CUtensorMap* m, int c0, int c1, uint32_t bar, uint64_t pol) {
  asm volatile(
      "cp.async.bulk.tensor.2d.shared::cluster.global.mbarrier::complete_tx::bytes.L2::cache_hint [%0], [%1, {%3, %4}], [%2], %5;"
      ::"r"(dst), "l"(m), "r"(bar), "r"(c0), "r"(c1), "l"(pol) : "memory");
}
__device__ __forceinline__ void tma3d(uint32_t dst, const CUtensorMap* m, int c0, int c1, int c2, uint32_t bar, uint64_t pol) {
  asm volatile(
      "cp.async.bulk.tensor.3d.shared::cluster.global.mbarrier::complete_tx::bytes.L2::cache_hint [%0], [%1, {%3, %4, %5}], [%2], %6;"
      ::"r"(dst), "l"(m), "r"(bar), "r"(c0), "r"(c1), "r"(c2), "l"(pol) : "memory");
}
__device__ __forceinline__ void tma4d(uint32_t dst, const CUtensorMap* m, int c0, int c1, int c2, int c3, uint32_t bar, uint64_t pol) {
  asm volatile(
      "cp.async.bulk.tensor.4d.shared::cluster.global.mbarrier::complete_tx::bytes.L2::cache_hint [%0], [%1, {%3, %4, %5, %6}], [%2], %7;"
      ::"r"(dst), "l"(m), "r"(bar), "r"(c0), "r"(c1), "r"(c2), "r"(c3), "l"(pol) : "memory");
}
__device__ __forceinline__ void cp_async16(uint32_t dst, const void* src) {
  asm volatile("cp.async.cg.shared.global.L2::128B [%0], [%1], 16;" ::"r"(dst), "l"(src) : "memory");
}
__device__ __forceinline__ void ldsm4(uint32_t (&r)[4], uint32_t addr) {
  asm volatile("ldmatrix.sync.aligned.m8n8.x4.shared.b16 {%0,%1,%2,%3}, [%4];"
               : "=r"(r[0]), "=r"(r[1]), "=r"(r[2]), "=r"(r[3]) : "r"(addr) : "memory");
}
__device__ __forceinline__ void ldsm4t(uint32_t (&r)[4], uint32_t addr) {
  asm volatile("ldmatrix.sync.aligned.m8n8.x4.trans.shared.b16 {%0,%1,%2,%3}, [%4];"
               : "=r"(r[0]), "=r"(r[1]), "=r"(r[2]), "=r"(r[3]) : "r"(addr) : "memory");
}
__device__ __forceinline__ void mma16816(float (&c)[4], const uint32_t (&a)[4], uint32_t b0, uint32_t b1) {
  asm(
      "mma.sync.aligned.m16n8k16.row.col.f32.bf16.bf16.f32 {%0,%1,%2,%3}, {%4,%5,%6,%7}, {%8,%9}, {%0,%1,%2,%3};"
      : "+f"(c[0]), "+f"(c[1]), "+f"(c[2]), "+f"(c[3])
      : "r"(a[0]), "r"(a[1]), "r"(a[2]), "r"(a[3]), "r"(b0), "r"(b1));
}
__device__ __forceinline__ uint32_t movmat(uint32_t a) {
  uint32_t d;
  asm volatile("movmatrix.sync.aligned.m8n8.trans.b16 %0, %1;" : "=r"(d) : "r"(a));
  return d;
}
__device__ __forceinline__ float ex2(float x) {
  float y;
  asm("ex2.approx.ftz.f32 %0, %1;" : "=f"(y) : "f"(x));
  return y;
}
__device__ __forceinline__ uint32_t pack_bf16(float lo, float hi) {
  uint32_t r;
  asm("cvt.rn.bf16x2.f32 %0, %1, %2;" : "=r"(r) : "f"(hi), "f"(lo));
  return r;
}
__device__ __forceinline__ float bf16r(float x) { return __bfloat162float(__float2bfloat16_rn(x)); }
__device__ __forceinline__ float silu_f(float x) { return x / (1.0f + __expf(-x)); }
__device__ __forceinline__ float warp_max(float x) {
  int i = __float_as_int(x);
  i ^= (i >> 31) & 0x7fffffff;
  i = __reduce_max_sync(0xffffffffu, i);
  i ^= (i >> 31) & 0x7fffffff;
  return __int_as_float(i);
}
__device__ __forceinline__ void bar_sync(int id, int n) { asm volatile("bar.sync %0, %1;" ::"r"(id), "r"(n) : "memory"); }
__device__ __forceinline__ void bar_arrive(int id, int n) { asm volatile("bar.arrive %0, %1;" ::"r"(id), "r"(n) : "memory"); }
__device__ __forceinline__ void red_release(unsigned* p, unsigned v) {
  asm volatile("red.release.gpu.global.add.u32 [%0], %1;" ::"l"(p), "r"(v) : "memory");
}
__device__ __forceinline__ void red_relaxed(unsigned* p, unsigned v) {
  asm volatile("red.relaxed.gpu.global.add.u32 [%0], %1;" ::"l"(p), "r"(v) : "memory");
}
__device__ __forceinline__ unsigned ld_acquire(const unsigned* p) {
  unsigned v;
  asm volatile("ld.acquire.gpu.global.u32 %0, [%1];" : "=r"(v) : "l"(p) : "memory");
  return v;
}
__device__ __forceinline__ unsigned atom_add(unsigned* p, unsigned v) {
  unsigned r;
  asm volatile("atom.relaxed.gpu.global.add.u32 %0, [%1], %2;" : "=r"(r) : "l"(p), "r"(v) : "memory");
  return r;
}
__device__ __forceinline__ void poll_ge(const unsigned* p, unsigned target, unsigned sleep_ns) {
  int it = 0;
  while (ld_acquire(p) < target) {
    if (sleep_ns) __nanosleep(sleep_ns);
    if (++it > kSpinLimit) __trap();
  }
}
__device__ __forceinline__ float4 ldx4(const float* p) {
  float4 v;
  asm volatile("ld.relaxed.gpu.global.v4.f32 {%0,%1,%2,%3}, [%4];" : "=f"(v.x), "=f"(v.y), "=f"(v.z), "=f"(v.w) : "l"(p) : "memory");
  return v;
}
__device__ __forceinline__ float nz(float v) { return __float_as_uint(v) == 0u ? -0.0f : v; }
__device__ __forceinline__ void stx4(float* p, float4 v) {
  asm volatile("st.relaxed.gpu.global.v4.f32 [%0], {%1,%2,%3,%4};" ::"l"(p), "f"(nz(v.x)), "f"(nz(v.y)), "f"(nz(v.z)), "f"(nz(v.w)) : "memory");
}
__device__ __forceinline__ void stx2(float* p, float a, float b) {
  asm volatile("st.relaxed.gpu.global.v2.f32 [%0], {%1,%2};" ::"l"(p), "f"(nz(a)), "f"(nz(b)) : "memory");
}
__device__ __forceinline__ void stx1(float* p, float a) {
  asm volatile("st.relaxed.gpu.global.f32 [%0], %1;" ::"l"(p), "f"(nz(a)) : "memory");
}
__device__ __forceinline__ void clr4(float* p) {
  asm volatile("st.relaxed.gpu.global.v4.f32 [%0], {%1,%1,%1,%1};" ::"l"(p), "f"(0.0f) : "memory");
}
__device__ __forceinline__ bool full4(const float4& v) {
  return __float_as_uint(v.x) != 0u && __float_as_uint(v.y) != 0u && __float_as_uint(v.z) != 0u && __float_as_uint(v.w) != 0u;
}
__device__ __forceinline__ void gather18(float4 (&v)[18], const float* po, const float* pml) {
#pragma unroll
  for (int k = 0; k < 18; k++) v[k] = ldx4(k < 16 ? po + k * 1024 : pml + (k - 16) * 128);
  for (int it = 0;; it++) {
    bool ok = true;
#pragma unroll
    for (int k = 0; k < 18; k++) ok = ok && full4(v[k]);
    if (__all_sync(0xffffffffu, ok)) break;
    if (it > kSpinLimit) __trap();
    __nanosleep(40);
#pragma unroll
    for (int k = 0; k < 18; k++)
      if (!full4(v[k])) v[k] = ldx4(k < 16 ? po + k * 1024 : pml + (k - 16) * 128);
  }
}

__device__ __forceinline__ void load_wo(uint32_t (&a)[18][4], uint32_t base, int w, int lane) {
  const uint32_t wl = ((lane & 7) + (lane >> 4) * 8) * 128 + ((((lane >> 3) & 1) ^ (lane & 7)) << 4);
#pragma unroll
  for (int mt = 0; mt < 9; mt++) {
    const int tile = w * 9 + mt;
    const uint32_t ad = base + (tile >> 2) * 4096 + (wl ^ ((tile & 3) << 5));
    ldsm4t(a[2 * mt], ad);
    ldsm4t(a[2 * mt + 1], ad + 2048);
  }
}

struct Maps {
  CUtensorMap wg, wu, wd, k, v, wo;
};

__global__ void __launch_bounds__(kThreads, 1)
fused_decode_kernel(const char* __restrict__ wqp, const __nv_bfloat16* __restrict__ x,
                    __nv_bfloat16* __restrict__ out, const __grid_constant__ Maps maps) {
  if (threadIdx.x == 224 && blockIdx.x < kSliceCtas)
    asm volatile("cp.async.bulk.prefetch.L2.global [%0], %1;" ::"l"(wqp + (size_t)blockIdx.x * 36864), "r"(36864) : "memory");
  extern __shared__ unsigned char smem_dyn[];
  unsigned char* sm = smem_dyn + ((1024u - (smem_u32(smem_dyn) & 1023u)) & 1023u);
  const uint32_t sb = smem_u32(sm);
  const int tid = threadIdx.x, warp = tid >> 5, lane = tid & 31;
  const int cta = blockIdx.x, G = gridDim.x;
  const uint32_t barFull = sb + kOffBar, barEmpty = barFull + kSlots * 8, barInfo = barEmpty + kSlots * 8;
  const uint32_t barMfull = barInfo + kSlots * 8, barMempty = barMfull + 16;
  const uint32_t barWo = barMempty + 16, barD = barWo + 8, barQ = barD + 8, barQok = barQ + 8;
  const uint32_t barFree = barQok + 8;
  volatile int* info = reinterpret_cast<volatile int*>(sm + kOffInfo);
  constexpr int kLastBatch = kNAtt - kHKV * kItemsPerPair;

  uint2 xr[9];
  if (warp < 4) {
    const uint2* xp = reinterpret_cast<const uint2*>(x + (warp * 2 + (lane >> 4)) * kD) + (lane & 15);
#pragma unroll
    for (int i = 0; i < 9; i++) xr[i] = __ldg(xp + i * 16);
    if (cta < kSliceCtas) {
      const uint32_t dst = sb + kOffW + warp * 9216 + (lane >> 2) * 64 + (((lane & 3) ^ ((lane >> 3) & 3)) << 4);
      const char* src = wqp + (size_t)(warp * 144 + (lane >> 2)) * 8192 + cta * 64 + (lane & 3) * 16;
#pragma unroll
      for (int i = 0; i < 18; i++) cp_async16(dst + i * 512, src + (size_t)i * 65536);
      asm volatile("cp.async.commit_group;" ::: "memory");
    }
  }
  if (warp == 5 && lane < 6)
    asm volatile("prefetch.tensormap [%0];" ::"l"(reinterpret_cast<const CUtensorMap*>(&maps) + lane) : "memory");
  unsigned nextDyn = 0;
  uint64_t pol = 0;
  if (tid == 128) {
    nextDyn = atom_add(&g_ctr.claim, 1);
#pragma unroll
    for (int i = 0; i < kNumBars; i++) {
      const int o = (i - 3 * kSlots) * 8;
      mbar_init(barFull + i * 8, (o == 0 || o == 8 || o == 40 || o == 48) ? 4 : 1);
    }
    asm volatile("fence.mbarrier_init.release.cluster;" ::: "memory");
    asm volatile("createpolicy.fractional.L2::evict_first.b64 %0, 1.0;" : "=l"(pol));
#pragma unroll
    for (int w = 0; w < kSlots; w++) {
      info[w] = cta;
      mbar_arrive(barInfo + w * 8);
      mbar_expect_tx(barFull + w * 8, 9216);
      tma2d(sb + kOffRing + w * kSlotBytes, w < 4 ? &maps.wg : &maps.wu, cta * 32, (w & 3) * 144, barFull + w * 8, pol);
    }
  }
  __syncthreads();

  if (warp >= 4) {
  if (warp == 4) {
    if (lane == 0) {
      int item = cta, n = kSlots;
      while (true) {
        const int nsub = item < kNFfn ? 12 : 4;
#pragma unroll 1
        for (int w = item == cta ? kSlots : 0; w < nsub; w++, n++) {
          const int slot = n & (kSlots - 1);
          mbar_wait(barEmpty + slot * 8, ((n / kSlots) & 1) ^ 1);
          info[slot] = item;
          mbar_arrive(barInfo + slot * 8);
          const uint32_t fb = barFull + slot * 8;
          const uint32_t dst = sb + kOffRing + slot * kSlotBytes;
          if (item >= kNFfn) {
            if (item < kNItems) {
              mbar_expect_tx(fb, kSlotBytes);
              const int row = (item - kNFfn) * kItemRows + w * 32;
              tma3d(dst, &maps.k, 0, row, 0, fb, pol);
              tma3d(dst + 8192, &maps.v, 0, row, 0, fb, pol);
            }
          } else {
            mbar_expect_tx(fb, 9216);
            const int c = (w & 3) * 144;
            if (w < 8) tma2d(dst, w < 4 ? &maps.wg : &maps.wu, item * 32, c, fb, pol);
            else tma2d(dst, &maps.wd, c, item * 32, fb, pol);
          }
        }
        if (item >= kNItems) break;
        if (item + G < kNFfn) {
          item += G;
          continue;
        }
        item = (int)nextDyn + kNFfn;
        if (item < kNItems) nextDyn = atom_add(&g_ctr.claim, 1);
      }
      if (cta < kSliceCtas) {
        mbar_wait(barFull + ((n - 5) & (kSlots - 1)) * 8, ((n - 5) / kSlots) & 1);
        mbar_expect_tx(barWo, 36864);
        tma4d(sb + kOffW, &maps.wo, 0, (cta & 7) * 16, (cta >> 3) * 2, 0, barWo, pol);
      }
    }
  } else if (warp == 5) {
    const float* mb = reinterpret_cast<const float*>(sm + kOffMbuf);
    int pend = -1;
    int batch = 0;
    if (lane == 0) {
      if (cta < kSliceCtas) {
        mbar_wait(barQ, 0);
        red_release(&g_ctr.qready, 1);
      }
      poll_ge(&g_ctr.qready, kSliceCtas, 50);
      mbar_arrive(barQok);
    }
    __syncwarp();
    for (int kk = 0;; kk++) {
      const int buf = kk & 1;
      mbar_wait(barMfull + buf * 8, (kk >> 1) & 1);
      const float* p = mb + buf * 4 * kMbufStride;
      const int item = __float_as_int(p[260]);
      if (pend >= 0 && lane == 0) red_release(&g_ctr.done[pend * 32], 1);
      if (item < 0) break;
      if ((item >> 10) != batch) {
        batch = item >> 10;
        if (batch >= 2) mbar_wait(barFree + (batch - 2) * 8, 0);
      }
      float4 ml[4];
#pragma unroll
      for (int w = 0; w < 4; w++) ml[w] = *reinterpret_cast<const float4*>(p + w * kMbufStride + 256);
      const float M0 = fmaxf(fmaxf(ml[0].x, ml[1].x), fmaxf(ml[2].x, ml[3].x));
      const float M1 = fmaxf(fmaxf(ml[0].z, ml[1].z), fmaxf(ml[2].z, ml[3].z));
      float4 a = make_float4(0.f, 0.f, 0.f, 0.f), b = a;
      float L0 = 0.f, L1 = 0.f;
#pragma unroll
      for (int w = 0; w < 4; w++) {
        const float s0 = ex2(ml[w].x - M0), s1 = ex2(ml[w].z - M1);
        L0 = fmaf(s0, ml[w].y, L0);
        L1 = fmaf(s1, ml[w].w, L1);
        const float4 u = *reinterpret_cast<const float4*>(p + w * kMbufStride + lane * 4);
        const float4 v = *reinterpret_cast<const float4*>(p + w * kMbufStride + 128 + lane * 4);
        a.x = fmaf(s0, u.x, a.x); a.y = fmaf(s1, u.y, a.y); a.z = fmaf(s0, u.z, a.z); a.w = fmaf(s1, u.w, a.w);
        b.x = fmaf(s0, v.x, b.x); b.y = fmaf(s1, v.y, b.y); b.z = fmaf(s0, v.z, b.z); b.w = fmaf(s1, v.w, b.w);
      }
      float* dst = g_po + (size_t)PSLOT(item >> 6) * (kItemsPerPair * 256) + (item & 63) * 256;
      stx4(dst + lane * 4, a);
      stx4(dst + 128 + lane * 4, b);
      if (lane < 8)
        stx4(reinterpret_cast<float*>(g_pml + (PSLOT(item >> 6) * 8 + lane) * kItemsPerPair + (item & 63)), make_float4(M0, L0, M1, L1));
      __syncwarp();
      pend = item >> 6;
      if (lane == 0) mbar_arrive(barMempty + buf * 8);
      if (item >= kLastBatch) pend = -1;
    }
  } else {
    const int cw = warp - 6;
    const int ci64 = tid - 192;
    mbar_wait(barQok, 0);
    if (ci64 == 0) {
      mbar_wait(barD, 0);
      red_release(&g_ctr.ddone, 1);
    }
    if (cta < kSliceCtas) {
      if (lane == 0) poll_ge(&g_ctr.ddone, G, 500);
      __syncwarp();
      float* ssum = reinterpret_cast<float*>(sm + kOffSsum);
      if (ci64 < 63) {
        const int q = ci64 % 9, pg = ci64 / 9;
        float4 acc = make_float4(0.f, 0.f, 0.f, 0.f);
#pragma unroll 4
        for (int p = pg; p < G; p += 7) {
          const float4 v = ldx4(g_dp + p * kOutElems + cta * 36 + q * 4);
          acc.x += v.x; acc.y += v.y; acc.z += v.z; acc.w += v.w;
        }
        *reinterpret_cast<float4*>(ssum + pg * 36 + q * 4) = acc;
      }
      float* g7 = reinterpret_cast<float*>(sm + kOffG7);
      if (cta < kRow7Ctas) {
        float acc = 0.f;
#pragma unroll 4
        for (int p = ci64 >> 3; p < G; p += 8) acc += __ldcg(g_dp + p * kOutElems + (cta * 8 + (ci64 & 7)) * 8 + 7);
        g7[ci64] = acc;
      }
      bar_sync(2, 64);
      if (cta < kRow7Ctas && ci64 >= 56) {
        float d = 0.f;
#pragma unroll
        for (int k = 0; k < 8; k++) d += g7[k * 8 + (ci64 & 7)];
        g7[64 + (ci64 & 7)] = bf16r(silu_f(bf16r(d)));
      }
      if (ci64 < 36) {
        float d = 0.f;
#pragma unroll
        for (int k = 0; k < 7; k++) d += ssum[k * 36 + ci64];
        ssum[252 + ci64] = bf16r(silu_f(bf16r(d)));
      }
      const int kvh = cta >> 3, sl = cta & 7;
      float2* wbuf = reinterpret_cast<float2*>(sm + kOffWbuf) + cw * 64;
      __nv_bfloat16* os = reinterpret_cast<__nv_bfloat16*>(sm + kOffOs);
      const int ci = lane >> 3, q4 = lane & 7;
#pragma unroll 1
      for (int b = cw; b < kB; b += 2) {
        const int pair = b * kHKV + kvh;
        if (b == 4 + cw) {
#pragma unroll 2
          for (int k = 0; k < 18; k++) clr4(g_sp + cta * kOutElems + (k * 64 + ci64) * 4);
          const int pair7 = PSLOT(7 * kHKV + kvh);
#pragma unroll 2
          for (int k = 0; k < 8; k++)
            clr4(g_po + ((size_t)pair7 * kItemsPerPair + k * 8 + (ci64 >> 3)) * 256 + sl * 32 + (ci64 & 7) * 4);
          clr4(reinterpret_cast<float*>(g_pml + (pair7 * 8 + sl) * kItemsPerPair + ci64));
          if (cta < kRow7Ctas) {
#pragma unroll
            for (int k = 0; k < 4; k++) clr4(g_s7 + cta * 1024 + (k * 64 + ci64) * 4);
          }
          __syncwarp();
          if (lane == 0) red_release(&g_ctr.zready, 1);
        }
        if (b >= 2 && lane == 0) {
          if (b == 7) poll_ge(&g_ctr.zready, kSliceCtas * 2, 200);
          else poll_ge(&g_ctr.cons[(b - 2) * 32], kSliceCtas, 200);
          mbar_arrive(barFree + (b - 2) * 8);
        }
        if (b == 7) break;
        const float* pml = reinterpret_cast<const float*>(g_pml + (PSLOT(pair) * 8 + sl) * kItemsPerPair);
        if (lane == 0) poll_ge(&g_ctr.done[pair * 32], kItemsPerPair, 300);
        __syncwarp();
        const float* po = g_po + (size_t)PSLOT(pair) * kItemsPerPair * 256 + sl * 32 + q4 * 4 + ci * 256;
        float4 v[18];
        gather18(v, po, pml + lane * 4);
        __syncwarp();
        if (lane == 0 && b < 5) red_release(&g_ctr.cons[b * 32], 1);
        const float4 mlA = v[16], mlB = v[17];
        const float M0 = warp_max(fmaxf(mlA.x, mlB.x)), M1 = warp_max(fmaxf(mlA.z, mlB.z));
        const float wA0 = ex2(mlA.x - M0), wA1 = ex2(mlA.z - M1), wB0 = ex2(mlB.x - M0), wB1 = ex2(mlB.z - M1);
        float L0 = wA0 * mlA.y + wB0 * mlB.y, L1 = wA1 * mlA.w + wB1 * mlB.w;
        wbuf[lane] = make_float2(wA0, wA1);
        wbuf[32 + lane] = make_float2(wB0, wB1);
        __syncwarp();
        float4 acc = make_float4(0.f, 0.f, 0.f, 0.f);
#pragma unroll
        for (int k = 0; k < 16; k++) {
          const float2 w2 = wbuf[k * 4 + ci];
          acc.x = fmaf(w2.x, v[k].x, acc.x); acc.y = fmaf(w2.y, v[k].y, acc.y);
          acc.z = fmaf(w2.x, v[k].z, acc.z); acc.w = fmaf(w2.y, v[k].w, acc.w);
        }
#pragma unroll
        for (int o = 1; o <= 16; o <<= 1) {
          L0 += __shfl_xor_sync(0xffffffffu, L0, o);
          L1 += __shfl_xor_sync(0xffffffffu, L1, o);
          if (o >= 8) {
            acc.x += __shfl_xor_sync(0xffffffffu, acc.x, o); acc.y += __shfl_xor_sync(0xffffffffu, acc.y, o);
            acc.z += __shfl_xor_sync(0xffffffffu, acc.z, o); acc.w += __shfl_xor_sync(0xffffffffu, acc.w, o);
          }
        }
        if (lane < 8) {
          const float r0 = 1.0f / L0, r1 = 1.0f / L1;
          *reinterpret_cast<uint32_t*>(os + b * 40 + q4 * 2) = pack_bf16(acc.x * r0, acc.z * r0);
          *reinterpret_cast<uint32_t*>(os + b * 40 + 16 + q4 * 2) = pack_bf16(acc.y * r1, acc.w * r1);
        }
        __syncwarp();
      }
      __syncwarp();
      if (cta < kRow7Ctas) bar_arrive(4, 192);
    } else if (lane == 0) {
      for (int b = 2 + cw; b < kB; b += 2) {
        if (b == 7) poll_ge(&g_ctr.zready, kSliceCtas * 2, 500);
        else poll_ge(&g_ctr.cons[(b - 2) * 32], kSliceCtas, 500);
        mbar_arrive(barFree + (b - 2) * 8);
      }
    }
  }
    __syncwarp();
    if (cta < kSliceCtas) {
      const int aw = warp - 4, at = tid - 128;
      const int g = lane >> 2, t = lane & 3;
      const int oe = cta * 36 + at;
      float xv = 0.f;
      if (at < 36) xv = __bfloat162float(x[(oe & 7) * kD + (oe >> 3)]);
      mbar_wait(barFree + 5 * 8, 0);
      mbar_wait(barWo, 0);
      uint32_t a[18][4];
      load_wo(a, sb + kOffW, aw, lane);
      bar_sync(3, 128);
      uint32_t ob[4] = {0u, 0u, 0u, 0u};
      if (g < 7) {
        const __nv_bfloat16* os = reinterpret_cast<const __nv_bfloat16*>(sm + kOffOs) + g * 40 + t * 2;
#pragma unroll
        for (int j = 0; j < 4; j++) ob[j] = *reinterpret_cast<const uint32_t*>(os + j * 8);
      }
#pragma unroll
      for (int mt = 0; mt < 9; mt++) {
        float c[4] = {0.f, 0.f, 0.f, 0.f};
        mma16816(c, a[2 * mt], ob[0], ob[1]);
        mma16816(c, a[2 * mt + 1], ob[2], ob[3]);
#pragma unroll
        for (int h = 0; h < 2; h++) {
          const int e = ((mt * 2 + h) * 8 + g) * 8 + t * 2, u = e / 36;
          stx2(g_sp + ((aw * 32 + u) * kSliceCtas + cta) * 36 + (e - u * 36), c[2 * h], c[2 * h + 1]);
        }
      }
      bar_sync(5, 256);
      const float* fp = g_sp + cta * kOutElems + at * 4;
      const int fcnt = at < 18 ? 10 : (at < 126 ? 9 : 0);
      float4 f[10];
#pragma unroll
      for (int k = 0; k < 10; k++) f[k] = k < fcnt ? ldx4(fp + k * 504) : make_float4(-0.f, -0.f, -0.f, -0.f);
      for (int it = 0;; it++) {
        bool ok = true;
#pragma unroll
        for (int k = 0; k < 10; k++) ok = ok && full4(f[k]);
        if (__all_sync(0xffffffffu, ok)) break;
        if (it > kSpinLimit) __trap();
        __nanosleep(40);
#pragma unroll
        for (int k = 0; k < 10; k++)
          if (!full4(f[k])) f[k] = ldx4(fp + k * 504);
      }
      float* fsum = reinterpret_cast<float*>(sm + kOffFsum);
      float4 acc = f[0];
#pragma unroll
      for (int k = 1; k < 10; k++) { acc.x += f[k].x; acc.y += f[k].y; acc.z += f[k].z; acc.w += f[k].w; }
      if (at < 126) *reinterpret_cast<float4*>(fsum + at * 4) = acc;
      bar_sync(3, 128);
      if (at < 36 && (oe & 7) != 7) {
        float s = 0.f;
#pragma unroll
        for (int k = 0; k < 14; k++) s += fsum[k * 36 + at];
        const float gt = reinterpret_cast<const float*>(sm + kOffSsum)[252 + at];
        out[(oe & 7) * kD + (oe >> 3)] = __float2bfloat16_rn(xv + bf16r(bf16r(s) * gt));
      }
    }
  } else {
    const int g = lane >> 2, t = lane & 3;
    __nv_bfloat16* xn = reinterpret_cast<__nv_bfloat16*>(sm + kOffXn);
    {
      float v[36];
#pragma unroll
      for (int i = 0; i < 9; i++) {
        v[4 * i] = __uint_as_float(xr[i].x << 16);
        v[4 * i + 1] = __uint_as_float(xr[i].x & 0xffff0000u);
        v[4 * i + 2] = __uint_as_float(xr[i].y << 16);
        v[4 * i + 3] = __uint_as_float(xr[i].y & 0xffff0000u);
      }
      float s = 0.f;
#pragma unroll
      for (int i = 0; i < 36; i++) s += v[i];
#pragma unroll
      for (int o = 8; o > 0; o >>= 1) s += __shfl_xor_sync(0xffffffffu, s, o);
      const float mean = s * (1.0f / kD);
      float q = 0.f;
#pragma unroll
      for (int i = 0; i < 36; i++) { const float d = v[i] - mean; q = fmaf(d, d, q); }
#pragma unroll
      for (int o = 8; o > 0; o >>= 1) q += __shfl_xor_sync(0xffffffffu, q, o);
      const float mb = bf16r(mean);
      const float rden = 1.0f / bf16r(sqrtf(bf16r(bf16r(q * (1.0f / kD)) + 1e-5f)));
      __nv_bfloat16* xw = xn + (warp * 2 + (lane >> 4)) * kXnPitch + (lane & 15) * 4;
#pragma unroll
      for (int i = 0; i < 9; i++)
        *reinterpret_cast<uint2*>(xw + i * 64) =
            make_uint2(pack_bf16(bf16r(v[4 * i] - mb) * rden, bf16r(v[4 * i + 1] - mb) * rden),
                       pack_bf16(bf16r(v[4 * i + 2] - mb) * rden, bf16r(v[4 * i + 3] - mb) * rden));
    }
    bar_sync(1, 128);
    float* mb = reinterpret_cast<float*>(sm + kOffMbuf);
    const uint32_t r8 = lane & 7;
    const uint32_t guLane = (r8 + (lane >> 4) * 8) * 64 + ((((lane >> 3) & 1) ^ (r8 >> 1)) << 4);
    int slot = warp, item;
    uint32_t fph = 0;
    {
      uint32_t xb[9][2];
#pragma unroll
      for (int ks = 0; ks < 9; ks++) {
        xb[ks][0] = *reinterpret_cast<const uint32_t*>(xn + g * kXnPitch + warp * 144 + ks * 16 + t * 2);
        xb[ks][1] = *reinterpret_cast<const uint32_t*>(xn + g * kXnPitch + warp * 144 + ks * 16 + 8 + t * 2);
      }
      if (cta < kSliceCtas) {
        if (tid == 0) {
          g_ctr.done[cta * 32] = 0;
          if (cta < 8) g_ctr.cons[cta * 32] = 0;
          if (cta == 0) { g_ctr.ddone = 0; g_ctr.zready = 0; g_ctr.exitc = 0; }
        }
        asm volatile("cp.async.wait_group 0;" ::: "memory");
        __syncwarp();
        const uint32_t lo = sb + kOffW + warp * 9216;
        uint32_t a[18][4];
#pragma unroll
        for (int i = 0; i < 18; i++) ldsm4t(a[i], lo + (guLane ^ ((i & 1) * 32)) + (i >> 1) * 1024);
        float c[2][4] = {{0.f, 0.f, 0.f, 0.f}, {0.f, 0.f, 0.f, 0.f}};
#pragma unroll
        for (int i = 0; i < 18; i++) mma16816(c[i & 1], a[i], xb[i >> 1][0], xb[i >> 1][1]);
        float* qr = mb + warp * 256;
#pragma unroll
        for (int mt = 0; mt < 2; mt++) {
          *reinterpret_cast<float2*>(qr + (mt * 16 + g) * 8 + t * 2) = make_float2(c[mt][0], c[mt][1]);
          *reinterpret_cast<float2*>(qr + (mt * 16 + 8 + g) * 8 + t * 2) = make_float2(c[mt][2], c[mt][3]);
        }
        bar_sync(1, 128);
        const int b = tid >> 4, cp = tid & 15;
        float q0 = 0.f, q1 = 0.f;
#pragma unroll
        for (int w = 0; w < 4; w++) {
          q0 += mb[w * 256 + (cp * 2) * 8 + b];
          q1 += mb[w * 256 + (cp * 2 + 1) * 8 + b];
        }
        const int col = cta * 32 + cp * 2;
        const int head = col >> 7, d = col & 127;
        const int pos = (head & 1) * 128 + (d >> 5) * 32 + ((d & 7) >> 1) * 8 + ((d >> 4) & 1) * 4 + ((d >> 3) & 1) * 2;
        *reinterpret_cast<uint32_t*>(g_q + (b * kHKV + (head >> 1)) * 256 + pos) = pack_bf16(q0, q1);
        __syncwarp();
        if (lane == 0) mbar_arrive(barQ);
      } else {
        bar_sync(1, 128);
      }

      float dacc[9][4];
#pragma unroll
      for (int i = 0; i < 9; i++) dacc[i][0] = dacc[i][1] = dacc[i][2] = dacc[i][3] = 0.f;
      float* red = reinterpret_cast<float*>(sm + kOffXn);
      const uint32_t dnLane = (r8 + (lane >> 4) * 8) * 288 + ((lane >> 3) & 1) * 16;
      while (true) {
        mbar_wait(barInfo + slot * 8, fph);
        item = info[slot];
        if (item >= kNFfn) break;
        uint32_t a[18][4];
        float* rw = red + warp * 512;
#pragma unroll 1
        for (int gu = 0; gu < 2; gu++) {
          mbar_wait(barFull + slot * 8, fph);
          const uint32_t base = sb + kOffRing + slot * kSlotBytes;
#pragma unroll
          for (int i = 0; i < 18; i++) ldsm4t(a[i], base + (guLane ^ ((i & 1) * 32)) + (i >> 1) * 1024);
          float c[2][4] = {{0.f, 0.f, 0.f, 0.f}, {0.f, 0.f, 0.f, 0.f}};
#pragma unroll
          for (int i = 0; i < 18; i++) mma16816(c[i & 1], a[i], xb[i >> 1][0], xb[i >> 1][1]);
#pragma unroll
          for (int mt = 0; mt < 2; mt++) {
            float* r = rw + gu * 256 + (2 * t) * 32 + mt * 16 + g;
            r[0] = c[mt][0]; r[32] = c[mt][1]; r[8] = c[mt][2]; r[40] = c[mt][3];
          }
          __syncwarp();
          if (lane == 0) mbar_arrive(barEmpty + slot * 8);
          slot += 4;
          if (slot >= kSlots) { slot -= kSlots; fph ^= 1; }
        }
        bar_sync(1, 128);
        uint32_t hb[4];
#pragma unroll
        for (int j = 0; j < 4; j++) {
          float2 gs = make_float2(0.f, 0.f), us = gs;
#pragma unroll
          for (int w = 0; w < 4; w++) {
            const float* rr = red + w * 512 + g * 32 + j * 8 + t * 2;
            const float2 a2 = *reinterpret_cast<const float2*>(rr), b2 = *reinterpret_cast<const float2*>(rr + 256);
            gs.x += a2.x; gs.y += a2.y; us.x += b2.x; us.y += b2.y;
          }
          hb[j] = pack_bf16(bf16r(silu_f(bf16r(gs.x))) * bf16r(us.x), bf16r(silu_f(bf16r(gs.y))) * bf16r(us.y));
        }
        mbar_wait(barFull + slot * 8, fph);
        const uint32_t base = sb + kOffRing + slot * kSlotBytes + dnLane;
#pragma unroll
        for (int i = 0; i < 18; i++) ldsm4t(a[i], base + (i >> 1) * 32 + (i & 1) * 4608);
#pragma unroll
        for (int i = 0; i < 18; i++) mma16816(dacc[i >> 1], a[i], hb[(i & 1) * 2], hb[(i & 1) * 2 + 1]);
        bar_sync(1, 128);
        if (lane == 0) mbar_arrive(barEmpty + slot * 8);
        slot += 4;
        if (slot >= kSlots) { slot -= kSlots; fph ^= 1; }
      }
      float* dp = g_dp + cta * kOutElems + (warp * 144 + g) * 8 + t * 2;
#pragma unroll
      for (int mt = 0; mt < 9; mt++) {
        *reinterpret_cast<float2*>(dp + mt * 128) = make_float2(dacc[mt][0], dacc[mt][1]);
        *reinterpret_cast<float2*>(dp + mt * 128 + 64) = make_float2(dacc[mt][2], dacc[mt][3]);
      }
      __syncwarp();
      if (lane == 0) mbar_arrive(barD);
      mbar_wait(barQok, 0);
    }

    const float kScale = 0.08838834764831845f * 1.4426950408889634f;
    const uint32_t kLane = (r8 + ((lane >> 3) & 1) * 8) * 128 + (((lane >> 4) ^ r8) << 4);
    const uint32_t vLane = 8192 + (r8 + (lane >> 4) * 8) * 128 + ((((lane >> 3) & 1) ^ r8) << 4);
    int kk = 0;
    while (item < kNItems) {
      item -= kNFfn;
      uint4 qv[4];
      if (g < 2) {
        const uint4* qs = reinterpret_cast<const uint4*>(g_q + (item >> 6) * 256 + g * 128 + t * 8);
#pragma unroll
        for (int i = 0; i < 4; i++) qv[i] = qs[i * 4];
      } else {
#pragma unroll
        for (int i = 0; i < 4; i++) qv[i] = make_uint4(0u, 0u, 0u, 0u);
      }
      mbar_wait(barFull + slot * 8, fph);
      const uint32_t base = sb + kOffRing + slot * kSlotBytes;
      uint32_t ka[16][4], va[16][4];
#pragma unroll
      for (int i = 0; i < 16; i++)
        ldsm4(ka[i], base + ((kLane ^ (((i >> 1) & 3) << 5)) + (i >> 3) * 4096 + (i & 1) * 2048));
#pragma unroll
      for (int i = 0; i < 16; i++)
        ldsm4t(va[i], base + ((vLane ^ (((i >> 1) & 3) << 5)) + (i >> 3) * 4096 + (i & 1) * 2048));
      float s[2][4], s2[2][4];
#pragma unroll
      for (int i = 0; i < 4; i++) s[0][i] = s[1][i] = s2[0][i] = s2[1][i] = 0.f;
#pragma unroll
      for (int kp = 0; kp < 4; kp++) {
        mma16816(s[0], ka[4 * kp], qv[kp].x, qv[kp].y);
        mma16816(s[1], ka[4 * kp + 1], qv[kp].x, qv[kp].y);
        mma16816(s2[0], ka[4 * kp + 2], qv[kp].z, qv[kp].w);
        mma16816(s2[1], ka[4 * kp + 3], qv[kp].z, qv[kp].w);
      }
#pragma unroll
      for (int i = 0; i < 4; i++) { s[0][i] += s2[0][i]; s[1][i] += s2[1][i]; }
      float m0 = fmaxf(fmaxf(s[0][0], s[0][2]), fmaxf(s[1][0], s[1][2]));
      float m1 = fmaxf(fmaxf(s[0][1], s[0][3]), fmaxf(s[1][1], s[1][3]));
#pragma unroll
      for (int o = 4; o <= 16; o <<= 1) {
        m0 = fmaxf(m0, __shfl_xor_sync(0xffffffffu, m0, o));
        m1 = fmaxf(m1, __shfl_xor_sync(0xffffffffu, m1, o));
      }
      m0 *= kScale; m1 *= kScale;
      float l0 = 0.f, l1 = 0.f;
      uint32_t pb[2][2];
#pragma unroll
      for (int mt = 0; mt < 2; mt++) {
        const float p0 = ex2(fmaf(s[mt][0], kScale, -m0)), p1 = ex2(fmaf(s[mt][1], kScale, -m1));
        const float p2 = ex2(fmaf(s[mt][2], kScale, -m0)), p3 = ex2(fmaf(s[mt][3], kScale, -m1));
        l0 += p0 + p2; l1 += p1 + p3;
        pb[mt][0] = movmat(pack_bf16(p0, p1));
        pb[mt][1] = movmat(pack_bf16(p2, p3));
      }
      float o_[8][4];
#pragma unroll
      for (int j = 0; j < 8; j++) {
        o_[j][0] = o_[j][1] = o_[j][2] = o_[j][3] = 0.f;
        mma16816(o_[j], va[2 * j], pb[0][0], pb[0][1]);
      }
#pragma unroll
      for (int j = 0; j < 8; j++) mma16816(o_[j], va[2 * j + 1], pb[1][0], pb[1][1]);
#pragma unroll
      for (int o = 4; o <= 16; o <<= 1) {
        l0 += __shfl_xor_sync(0xffffffffu, l0, o);
        l1 += __shfl_xor_sync(0xffffffffu, l1, o);
      }
      const int buf = kk & 1;
      mbar_wait(barMempty + buf * 8, ((kk >> 1) & 1) ^ 1);
      float* p = mb + (buf * 4 + warp) * kMbufStride;
      if (t == 0) {
#pragma unroll
        for (int j = 0; j < 8; j++) {
          *reinterpret_cast<float2*>(p + (j * 16 + g) * 2) = make_float2(o_[j][0], o_[j][1]);
          *reinterpret_cast<float2*>(p + (j * 16 + 8 + g) * 2) = make_float2(o_[j][2], o_[j][3]);
        }
        if (g == 0) {
          *reinterpret_cast<float4*>(p + 256) = make_float4(m0, l0, m1, l1);
          p[260] = __int_as_float(item);
        }
      }
      __syncwarp();
      if (lane == 0) {
        mbar_arrive(barMfull + buf * 8);
        mbar_arrive(barEmpty + slot * 8);
      }
      kk++;
      slot += 4;
      if (slot >= kSlots) { slot -= kSlots; fph ^= 1; }
      mbar_wait(barInfo + slot * 8, fph);
      item = info[slot];
    }
    {
      const int buf = kk & 1;
      mbar_wait(barMempty + buf * 8, ((kk >> 1) & 1) ^ 1);
      if (lane == 0) {
        mb[(buf * 4 + warp) * kMbufStride + 260] = __int_as_float(-1);
        mbar_arrive(barMfull + buf * 8);
        if (warp == 0) red_relaxed(&g_ctr.exitc, 1);
      }
      __syncwarp();
    }
    if (cta < kSliceCtas) {
      float xv = 0.f;
      if (tid < 8 && cta < kRow7Ctas) xv = __bfloat162float(x[7 * kD + cta * 8 + tid]);
      mbar_wait(barFree + 5 * 8, 0);
      const int ps = PSLOT(7 * kHKV + (cta >> 3)), sl = cta & 7;
      const int ci = lane >> 3, q4 = lane & 7;
      const float* po = g_po + (ps * kItemsPerPair + warp * 16 + ci) * 256 + sl * 32 + q4 * 4;
      const float* pml = reinterpret_cast<const float*>(g_pml + (ps * 8 + sl) * kItemsPerPair + warp * 16 + (lane & 15));
      float4 v[5];
#pragma unroll
      for (int k = 0; k < 5; k++) v[k] = ldx4(k < 4 ? po + k * 1024 : pml);
      uint32_t a[18][4], ob[4];
      bool haveWo = false;
      for (int it = 0;; it++) {
        if (!haveWo && __all_sync(0xffffffffu, mbar_test(barWo, 0))) {
          load_wo(a, sb + kOffW, warp, lane);
          haveWo = true;
        }
        bool ok = true;
#pragma unroll
        for (int k = 0; k < 5; k++) ok = ok && full4(v[k]);
        if (__all_sync(0xffffffffu, ok) && haveWo) break;
        if (it > kSpinLimit) __trap();
#pragma unroll
        for (int k = 0; k < 5; k++)
          if (!full4(v[k])) v[k] = ldx4(k < 4 ? po + k * 1024 : pml);
      }
      float* cb = reinterpret_cast<float*>(sm + kOffCbuf);
      {
        const float M0 = warp_max(v[4].x), M1 = warp_max(v[4].z);
        const float w0 = ex2(v[4].x - M0), w1 = ex2(v[4].z - M1);
        float L0 = w0 * v[4].y, L1 = w1 * v[4].w;
        float4 acc = make_float4(0.f, 0.f, 0.f, 0.f);
#pragma unroll
        for (int k = 0; k < 4; k++) {
          const float a0 = __shfl_sync(0xffffffffu, w0, k * 4 + ci), a1 = __shfl_sync(0xffffffffu, w1, k * 4 + ci);
          acc.x = fmaf(a0, v[k].x, acc.x); acc.y = fmaf(a1, v[k].y, acc.y);
          acc.z = fmaf(a0, v[k].z, acc.z); acc.w = fmaf(a1, v[k].w, acc.w);
        }
#pragma unroll
        for (int o = 1; o <= 16; o <<= 1) {
          if (o <= 8) {
            L0 += __shfl_xor_sync(0xffffffffu, L0, o);
            L1 += __shfl_xor_sync(0xffffffffu, L1, o);
          }
          if (o >= 8) {
            acc.x += __shfl_xor_sync(0xffffffffu, acc.x, o); acc.y += __shfl_xor_sync(0xffffffffu, acc.y, o);
            acc.z += __shfl_xor_sync(0xffffffffu, acc.z, o); acc.w += __shfl_xor_sync(0xffffffffu, acc.w, o);
          }
        }
        if (lane < 8) {
          *reinterpret_cast<float2*>(cb + warp * 40 + q4 * 2) = make_float2(acc.x, acc.z);
          *reinterpret_cast<float2*>(cb + warp * 40 + 16 + q4 * 2) = make_float2(acc.y, acc.w);
          if (lane == 0) *reinterpret_cast<float4*>(cb + warp * 40 + 32) = make_float4(M0, L0, M1, L1);
        }
      }
      bar_sync(1, 128);
      {
        float4 ml[4];
#pragma unroll
        for (int w = 0; w < 4; w++) ml[w] = *reinterpret_cast<const float4*>(cb + w * 40 + 32);
        const float M0 = fmaxf(fmaxf(ml[0].x, ml[1].x), fmaxf(ml[2].x, ml[3].x));
        const float M1 = fmaxf(fmaxf(ml[0].z, ml[1].z), fmaxf(ml[2].z, ml[3].z));
        float L0 = 0.f, L1 = 0.f;
        float2 o2[4] = {{0.f, 0.f}, {0.f, 0.f}, {0.f, 0.f}, {0.f, 0.f}};
#pragma unroll
        for (int w = 0; w < 4; w++) {
          const float s0 = ex2(ml[w].x - M0), s1 = ex2(ml[w].z - M1);
          L0 = fmaf(s0, ml[w].y, L0);
          L1 = fmaf(s1, ml[w].w, L1);
#pragma unroll
          for (int j = 0; j < 4; j++) {
            const float2 u = *reinterpret_cast<const float2*>(cb + w * 40 + j * 8 + t * 2);
            o2[j].x = fmaf(j < 2 ? s0 : s1, u.x, o2[j].x);
            o2[j].y = fmaf(j < 2 ? s0 : s1, u.y, o2[j].y);
          }
        }
        const float r0 = __frcp_rn(L0), r1 = __frcp_rn(L1);
#pragma unroll
        for (int j = 0; j < 4; j++) ob[j] = pack_bf16(o2[j].x * (j < 2 ? r0 : r1), o2[j].y * (j < 2 ? r0 : r1));
      }
      {
        float c[10][4];
#pragma unroll
        for (int mt = 0; mt < 9; mt++) {
          c[mt][0] = c[mt][1] = c[mt][2] = c[mt][3] = 0.f;
          mma16816(c[mt], a[2 * mt], ob[0], ob[1]);
          mma16816(c[mt], a[2 * mt + 1], ob[2], ob[3]);
        }
        c[9][0] = c[9][2] = 0.f;
        float* s7 = g_s7 + ((warp * 18 + t) * kSliceCtas + cta) * 8 + g;
#pragma unroll
        for (int k = 0; k < 5; k++) {
          const float lo = (t & 1) ? c[2 * k][2] : c[2 * k][0], hi = (t & 1) ? c[2 * k + 1][2] : c[2 * k + 1][0];
          if (k < 4 || t < 2) stx1(s7 + k * 4 * kSliceCtas * 8, (t & 2) ? hi : lo);
        }
      }
      bar_arrive(5, 256);
      if (cta < kRow7Ctas) {
        const float* hp = g_s7 + cta * 1024 + tid * 4;
        float4 f0 = ldx4(hp), f1 = ldx4(hp + 512);
        for (int it = 0; !__all_sync(0xffffffffu, full4(f0) && full4(f1)); it++) {
          if (it > kSpinLimit) __trap();
          if (!full4(f0)) f0 = ldx4(hp);
          if (!full4(f1)) f1 = ldx4(hp + 512);
        }
        float* g7 = reinterpret_cast<float*>(sm + kOffG7);
        float4 h = make_float4(f0.x + f1.x, f0.y + f1.y, f0.z + f1.z, f0.w + f1.w);
#pragma unroll
        for (int o = 2; o <= 16; o <<= 1) {
          h.x += __shfl_xor_sync(0xffffffffu, h.x, o); h.y += __shfl_xor_sync(0xffffffffu, h.y, o);
          h.z += __shfl_xor_sync(0xffffffffu, h.z, o); h.w += __shfl_xor_sync(0xffffffffu, h.w, o);
        }
        if (lane < 2) *reinterpret_cast<float4*>(g7 + 72 + warp * 8 + lane * 4) = h;
        bar_sync(4, 192);
        if (tid < 8) {
          const float s = (g7[72 + tid] + g7[80 + tid]) + (g7[88 + tid] + g7[96 + tid]);
          out[7 * kD + cta * 8 + tid] = __float2bfloat16_rn(xv + bf16r(bf16r(s) * g7[64 + tid]));
        }
      }
      if (cta == 0 && tid == 96) {
        poll_ge(&g_ctr.exitc, G, 20);
        g_ctr.claim = 0;
        g_ctr.qready = 0;
      }
    }
  }
}

__global__ void fb_ln(const __nv_bfloat16* x, float* xn) {
  const int lane = threadIdx.x;
  const __nv_bfloat16* xr = x + blockIdx.x * kD;
  float s = 0.f, q = 0.f;
  for (int i = lane; i < kD; i += 32) s += __bfloat162float(xr[i]);
  for (int o = 16; o > 0; o >>= 1) s += __shfl_xor_sync(0xffffffffu, s, o);
  const float mean = s * (1.0f / kD);
  for (int i = lane; i < kD; i += 32) { const float d = __bfloat162float(xr[i]) - mean; q = fmaf(d, d, q); }
  for (int o = 16; o > 0; o >>= 1) q += __shfl_xor_sync(0xffffffffu, q, o);
  const float den = bf16r(sqrtf(bf16r(bf16r(q * (1.0f / kD)) + 1e-5f)));
  for (int i = lane; i < kD; i += 32) xn[blockIdx.x * kD + i] = bf16r(bf16r(__bfloat162float(xr[i]) - bf16r(mean)) / den);
}
__global__ void fb_gemv(const float* a, const float* a2, const __nv_bfloat16* w, float* o, int K, int N) {
  const int n = blockIdx.x * 64 + threadIdx.x, b = blockIdx.y;
  float s = 0.f;
  for (int k = 0; k < K; k++) {
    const float v = a2 ? bf16r(bf16r(silu_f(a[b * K + k])) * a2[b * K + k]) : a[b * K + k];
    s = fmaf(v, __bfloat162float(w[(size_t)k * N + n]), s);
  }
  o[b * N + n] = bf16r(s);
}
__global__ void fb_att(const float* q, const __nv_bfloat16* kc, const __nv_bfloat16* vc, float* o) {
  __shared__ float sm_[8][132];
  const int warp = threadIdx.x >> 5, lane = threadIdx.x & 31;
  const size_t base = (size_t)(blockIdx.x >> 1) * kSK * 128 + lane * 4;
  float qv[4], acc[4] = {0.f, 0.f, 0.f, 0.f}, m = -INFINITY, l = 0.f;
  for (int i = 0; i < 4; i++) qv[i] = q[blockIdx.x * 128 + lane * 4 + i];
  for (int j = warp; j < kSK; j += 8) {
    float s = 0.f;
    for (int i = 0; i < 4; i++) s = fmaf(qv[i], __bfloat162float(kc[base + (size_t)j * 128 + i]), s);
    for (int x = 16; x > 0; x >>= 1) s += __shfl_xor_sync(0xffffffffu, s, x);
    s *= 0.08838834764831845f;
    const float mn = fmaxf(m, s), c = __expf(m - mn), pr = __expf(s - mn);
    l = l * c + pr;
    for (int i = 0; i < 4; i++) acc[i] = acc[i] * c + pr * __bfloat162float(vc[base + (size_t)j * 128 + i]);
    m = mn;
  }
  for (int i = 0; i < 4; i++) sm_[warp][lane * 4 + i] = acc[i];
  if (lane == 0) { sm_[warp][128] = m; sm_[warp][129] = l; }
  __syncthreads();
  if (threadIdx.x < 128) {
    float M = -INFINITY, L = 0.f, r = 0.f;
    for (int w = 0; w < 8; w++) M = fmaxf(M, sm_[w][128]);
    for (int w = 0; w < 8; w++) { const float c = __expf(sm_[w][128] - M); L += c * sm_[w][129]; r += c * sm_[w][threadIdx.x]; }
    o[blockIdx.x * 128 + threadIdx.x] = bf16r(r / L);
  }
}
__global__ void fb_out(const __nv_bfloat16* x, const float* s, const float* d, __nv_bfloat16* out) {
  const int i = blockIdx.x * 64 + threadIdx.x;
  out[i] = __float2bfloat16_rn(__bfloat162float(x[i]) + bf16r(s[i] * bf16r(silu_f(d[i]))));
}

typedef CUresult (*EncodeFn)(CUtensorMap*, CUtensorMapDataType, cuuint32_t, void*, const cuuint64_t*,
                             const cuuint64_t*, const cuuint32_t*, const cuuint32_t*, CUtensorMapInterleave,
                             CUtensorMapSwizzle, CUtensorMapL2promotion, CUtensorMapFloatOOBfill);

void encode(EncodeFn fn, CUtensorMap* m, const void* base, int rank, const cuuint64_t* dims, const cuuint64_t* strides,
            const cuuint32_t* box, CUtensorMapSwizzle sw,
            CUtensorMapL2promotion promo = CU_TENSOR_MAP_L2_PROMOTION_L2_128B) {
  const cuuint32_t es[4] = {1, 1, 1, 1};
  fn(m, CU_TENSOR_MAP_DATA_TYPE_BFLOAT16, rank, const_cast<void*>(base), dims, strides, box, es,
     CU_TENSOR_MAP_INTERLEAVE_NONE, sw, promo, CU_TENSOR_MAP_FLOAT_OOB_FILL_NONE);
}

}

extern "C" void kernel_launch(void* const* d_in, const int* in_sizes, int n_in, void* d_out, int out_size) {
  (void)in_sizes; (void)n_in; (void)out_size;
  static EncodeFn fn = nullptr;
  static int sms = 0;
  if (!sms) {
    void* p = nullptr;
    cudaDriverEntryPointQueryResult qr;
    cudaGetDriverEntryPoint("cuTensorMapEncodeTiled", &p, cudaEnableDefault, &qr);
    fn = (EncodeFn)p;
    int dev = 0;
    cudaGetDevice(&dev);
    cudaDeviceGetAttribute(&sms, cudaDevAttrMultiProcessorCount, dev);
    cudaFuncSetAttribute(fused_decode_kernel, cudaFuncAttributeMaxDynamicSharedMemorySize, kSmemBytes);
  }
  if (sms < kSliceCtas || !fn) {
    typedef const __nv_bfloat16* P;
    float* t = nullptr;
    cudaGetSymbolAddress((void**)&t, g_po);
    float *xn = t, *q = t + 8192, *o = q + 32768, *g = o + 32768, *u = g + 36864, *sv = u + 36864, *d = sv + 8192;
    fb_ln<<<kB, 32>>>((P)d_in[0], xn);
    fb_gemv<<<dim3(64, kB), 64>>>(xn, nullptr, (P)d_in[3], q, kD, 4096);
    fb_att<<<256, 256>>>(q, (P)d_in[1], (P)d_in[2], o);
    fb_gemv<<<dim3(9, kB), 64>>>(o, nullptr, (P)d_in[4], sv, 4096, kD);
    fb_gemv<<<dim3(72, kB), 64>>>(xn, nullptr, (P)d_in[6], g, kD, kF);
    fb_gemv<<<dim3(72, kB), 64>>>(xn, nullptr, (P)d_in[7], u, kD, kF);
    fb_gemv<<<dim3(9, kB), 64>>>(g, u, (P)d_in[8], d, kF, kD);
    fb_out<<<72, 64>>>((P)d_in[0], sv, d, (__nv_bfloat16*)d_out);
    return;
  }
  Maps maps;
  {
    const cuuint64_t dims[3] = {64, (cuuint64_t)kPairs * kSK, 2}, str[2] = {256, 128};
    const cuuint32_t box[3] = {64, 32, 2};
    encode(fn, &maps.k, d_in[1], 3, dims, str, box, CU_TENSOR_MAP_SWIZZLE_128B, CU_TENSOR_MAP_L2_PROMOTION_L2_256B);
    encode(fn, &maps.v, d_in[2], 3, dims, str, box, CU_TENSOR_MAP_SWIZZLE_128B, CU_TENSOR_MAP_L2_PROMOTION_L2_256B);
  }
  {
    const cuuint64_t dims[4] = {64, 128, 32, 9}, str[3] = {kD * 2, 128 * kD * 2, 128};
    const cuuint32_t box[4] = {64, 16, 2, 9};
    encode(fn, &maps.wo, d_in[4], 4, dims, str, box, CU_TENSOR_MAP_SWIZZLE_128B);
  }
  {
    const cuuint64_t dims[2] = {kF, kD}, str[1] = {kF * 2};
    const cuuint32_t box[2] = {32, 144};
    encode(fn, &maps.wg, d_in[6], 2, dims, str, box, CU_TENSOR_MAP_SWIZZLE_64B);
    encode(fn, &maps.wu, d_in[7], 2, dims, str, box, CU_TENSOR_MAP_SWIZZLE_64B);
  }
  {
    const cuuint64_t dims[2] = {kD, kF}, str[1] = {kD * 2};
    const cuuint32_t box[2] = {144, 32};
    encode(fn, &maps.wd, d_in[8], 2, dims, str, box, CU_TENSOR_MAP_SWIZZLE_NONE);
  }
  int grid = sms < kMaxCtas ? sms : kMaxCtas;
  fused_decode_kernel<<<grid, kThreads, kSmemBytes>>>((const char*)d_in[3], (const __nv_bfloat16*)d_in[0],
                                                      (__nv_bfloat16*)d_out, maps);
}
```

```cpp
#include <cuda_runtime.h>
#include <cuda_bf16.h>
#include <cuda.h>
#include <stddef.h>
#include <stdint.h>

namespace {

constexpr int kB = 8, kD = 576, kHKV = 16, kSK = 8192, kF = 4608;
constexpr int kPairs = kB * kHKV;
constexpr int kItemRows = 128;
constexpr int kItemsPerPair = kSK / kItemRows;
constexpr int kNAtt = kPairs * kItemsPerPair;
constexpr int kNFfn = kF / 32;
constexpr int kNItems = kNAtt + kNFfn;
constexpr int kSlots = 8;
constexpr int kSlotBytes = 16384;
constexpr int kMaxCtas = kNFfn;
constexpr int kSliceCtas = 128;
constexpr int kRow7Ctas = 72;
constexpr int kThreads = 256;
constexpr int kOutElems = kB * kD;

constexpr int kOffRing = 0;
constexpr int kOffW = kOffRing + kSlots * kSlotBytes;
constexpr int kOffXn = kOffW + 36864;
constexpr int kXnPitch = 584;
constexpr int kOffMbuf = kOffXn + kB * kXnPitch * 2;
constexpr int kMbufStride = 264;
constexpr int kOffOs = kOffMbuf + 2 * 4 * kMbufStride * 4;
constexpr int kOffWbuf = kOffOs + 8 * 40 * 2;
constexpr int kOffFsum = kOffWbuf + 2 * 64 * 8;
constexpr int kOffSsum = kOffFsum + 14 * 36 * 4;
constexpr int kOffG7 = kOffSsum + 8 * 36 * 4;
constexpr int kOffCbuf = kOffG7 + 104 * 4;
constexpr int kOffInfo = kOffCbuf + 4 * 40 * 4;
constexpr int kOffBar = kOffInfo + 64;
constexpr int kNumBars = 3 * kSlots + 8 + 6;
constexpr unsigned long long kBarCount4 = 0x63ull << (3 * kSlots);
constexpr int kSmemBytes = kOffBar + kNumBars * 8 + 1024;
static_assert(kSmemBytes <= 232448, "smem");

constexpr int kPartSlots = 48;
__device__ __forceinline__ int PSLOT(int pair) { return pair >= 112 ? pair - 112 : 16 + (pair & 31); }

struct Counters {
  unsigned claim;
  unsigned qready; unsigned pad1[30];
  unsigned ddone;  unsigned pad2[31];
  unsigned zready; unsigned pad3[31];
  unsigned exitc;  unsigned pad4[31];
  unsigned cons[8 * 32];
  unsigned done[kPairs * 32];
};

struct Scratch {
  Counters ctr;
  alignas(128) __nv_bfloat16 q[kPairs * 256];
  alignas(128) float4 pml[kPartSlots * 8 * kItemsPerPair];
  alignas(128) float s7[kRow7Ctas * kSliceCtas * 8];
  alignas(128) float po[kPartSlots * kItemsPerPair * 256];
  alignas(128) float sp[kSliceCtas * kOutElems];
  alignas(128) float dp[kMaxCtas * kOutElems];
};
static_assert(offsetof(Scratch, po) + 16 * kItemsPerPair * 1024 <= (2u << 20), "batch-7 partials in the first page");
__device__ __align__(128) unsigned char g_raw[sizeof(Scratch) + (2u << 20)];

constexpr int kSpinLimit = 1 << 21;

__device__ __forceinline__ uint32_t smem_u32(const void* p) { return (uint32_t)__cvta_generic_to_shared(p); }
__device__ __forceinline__ void mbar_init(uint32_t bar, uint32_t cnt) {
  asm volatile("mbarrier.init.shared::cta.b64 [%0], %1;" ::"r"(bar), "r"(cnt) : "memory");
}
__device__ __forceinline__ void mbar_expect_tx(uint32_t bar, uint32_t bytes) {
  asm volatile("mbarrier.arrive.expect_tx.shared::cta.b64 _, [%0], %1;" ::"r"(bar), "r"(bytes) : "memory");
}
__device__ __forceinline__ void mbar_arrive(uint32_t bar) {
  asm volatile("mbarrier.arrive.shared::cta.b64 _, [%0];" ::"r"(bar) : "memory");
}
__device__ __forceinline__ void mbar_wait(uint32_t bar, uint32_t parity) {
  uint32_t done;
  int it = 0;
  do {
    asm volatile(
        "{\n.reg .pred p;\nmbarrier.try_wait.parity.shared::cta.b64 p, [%1], %2;\nselp.u32 %0, 1, 0, p;\n}"
        : "=r"(done) : "r"(bar), "r"(parity) : "memory");
    if (++it > kSpinLimit) __trap();
  } while (!done);
}
__device__ __forceinline__ bool mbar_test(uint32_t bar, uint32_t parity) {
  uint32_t done;
  asm volatile(
      "{\n.reg .pred p;\nmbarrier.test_wait.parity.shared::cta.b64 p, [%1], %2;\nselp.u32 %0, 1, 0, p;\n}"
      : "=r"(done) : "r"(bar), "r"(parity) : "memory");
  return done != 0;
}
__device__ __forceinline__ void tma2d(uint32_t dst, const CUtensorMap* m, int c0, int c1, uint32_t bar, uint64_t pol) {
  asm volatile(
      "cp.async.bulk.tensor.2d.shared::cluster.global.mbarrier::complete_tx::bytes.L2::cache_hint [%0], [%1, {%3, %4}], [%2], %5;"
      ::"r"(dst), "l"(m), "r"(bar), "r"(c0), "r"(c1), "l"(pol) : "memory");
}
__device__ __forceinline__ void tma3d(uint32_t dst, const CUtensorMap* m, int c0, int c1, int c2, uint32_t bar, uint64_t pol) {
  asm volatile(
      "cp.async.bulk.tensor.3d.shared::cluster.global.mbarrier::complete_tx::bytes.L2::cache_hint [%0], [%1, {%3, %4, %5}], [%2], %6;"
      ::"r"(dst), "l"(m), "r"(bar), "r"(c0), "r"(c1), "r"(c2), "l"(pol) : "memory");
}
__device__ __forceinline__ void tma4d(uint32_t dst, const CUtensorMap* m, int c0, int c1, int c2, int c3, uint32_t bar, uint64_t pol) {
  asm volatile(
      "cp.async.bulk.tensor.4d.shared::cluster.global.mbarrier::complete_tx::bytes.L2::cache_hint [%0], [%1, {%3, %4, %5, %6}], [%2], %7;"
      ::"r"(dst), "l"(m), "r"(bar), "r"(c0), "r"(c1), "r"(c2), "r"(c3), "l"(pol) : "memory");
}
__device__ __forceinline__ void cp_async16(uint32_t dst, const void* src) {
  asm volatile("cp.async.cg.shared.global.L2::128B [%0], [%1], 16;" ::"r"(dst), "l"(src) : "memory");
}
__device__ __forceinline__ void ldsm4(uint32_t (&r)[4], uint32_t addr) {
  asm volatile("ldmatrix.sync.aligned.m8n8.x4.shared.b16 {%0,%1,%2,%3}, [%4];"
               : "=r"(r[0]), "=r"(r[1]), "=r"(r[2]), "=r"(r[3]) : "r"(addr) : "memory");
}
__device__ __forceinline__ void ldsm4t(uint32_t (&r)[4], uint32_t addr) {
  asm volatile("ldmatrix.sync.aligned.m8n8.x4.trans.shared.b16 {%0,%1,%2,%3}, [%4];"
               : "=r"(r[0]), "=r"(r[1]), "=r"(r[2]), "=r"(r[3]) : "r"(addr) : "memory");
}
__device__ __forceinline__ void mma16816(float (&c)[4], const uint32_t (&a)[4], uint32_t b0, uint32_t b1) {
  asm(
      "mma.sync.aligned.m16n8k16.row.col.f32.bf16.bf16.f32 {%0,%1,%2,%3}, {%4,%5,%6,%7}, {%8,%9}, {%0,%1,%2,%3};"
      : "+f"(c[0]), "+f"(c[1]), "+f"(c[2]), "+f"(c[3])
      : "r"(a[0]), "r"(a[1]), "r"(a[2]), "r"(a[3]), "r"(b0), "r"(b1));
}
__device__ __forceinline__ uint32_t movmat(uint32_t a) {
  uint32_t d;
  asm volatile("movmatrix.sync.aligned.m8n8.trans.b16 %0, %1;" : "=r"(d) : "r"(a));
  return d;
}
__device__ __forceinline__ float ex2(float x) {
  float y;
  asm("ex2.approx.ftz.f32 %0, %1;" : "=f"(y) : "f"(x));
  return y;
}
__device__ __forceinline__ uint32_t pack_bf16(float lo, float hi) {
  uint32_t r;
  asm("cvt.rn.bf16x2.f32 %0, %1, %2;" : "=r"(r) : "f"(hi), "f"(lo));
  return r;
}
__device__ __forceinline__ float bf16r(float x) { return __bfloat162float(__float2bfloat16_rn(x)); }
__device__ __forceinline__ float silu_f(float x) { return x / (1.0f + __expf(-x)); }
__device__ __forceinline__ float warp_max(float x) {
  int i = __float_as_int(x);
  i ^= (i >> 31) & 0x7fffffff;
  i = __reduce_max_sync(0xffffffffu, i);
  i ^= (i >> 31) & 0x7fffffff;
  return __int_as_float(i);
}
__device__ __forceinline__ void bar_sync(int id, int n) { asm volatile("bar.sync %0, %1;" ::"r"(id), "r"(n) : "memory"); }
__device__ __forceinline__ void bar_arrive(int id, int n) { asm volatile("bar.arrive %0, %1;" ::"r"(id), "r"(n) : "memory"); }
__device__ __forceinline__ void red_release(unsigned* p, unsigned v) {
  asm volatile("red.release.gpu.global.add.u32 [%0], %1;" ::"l"(p), "r"(v) : "memory");
}
__device__ __forceinline__ void red_relaxed(unsigned* p, unsigned v) {
  asm volatile("red.relaxed.gpu.global.add.u32 [%0], %1;" ::"l"(p), "r"(v) : "memory");
}
__device__ __forceinline__ unsigned ld_acquire(const unsigned* p) {
  unsigned v;
  asm volatile("ld.acquire.gpu.global.u32 %0, [%1];" : "=r"(v) : "l"(p) : "memory");
  return v;
}
__device__ __forceinline__ unsigned atom_add(unsigned* p, unsigned v) {
  unsigned r;
  asm volatile("atom.relaxed.gpu.global.add.u32 %0, [%1], %2;" : "=r"(r) : "l"(p), "r"(v) : "memory");
  return r;
}
__device__ __forceinline__ void poll_ge(const unsigned* p, unsigned target, unsigned sleep_ns) {
  int it = 0;
  while (ld_acquire(p) < target) {
    if (sleep_ns) __nanosleep(sleep_ns);
    if (++it > kSpinLimit) __trap();
  }
}
__device__ __forceinline__ float4 ldx4(const float* p) {
  float4 v;
  asm volatile("ld.relaxed.gpu.global.v4.f32 {%0,%1,%2,%3}, [%4];" : "=f"(v.x), "=f"(v.y), "=f"(v.z), "=f"(v.w) : "l"(p) : "memory");
  return v;
}
__device__ __forceinline__ float nz(float v) { return __float_as_uint(v) == 0u ? -0.0f : v; }
__device__ __forceinline__ void stx4(float* p, float4 v) {
  asm volatile("st.relaxed.gpu.global.v4.f32 [%0], {%1,%2,%3,%4};" ::"l"(p), "f"(nz(v.x)), "f"(nz(v.y)), "f"(nz(v.z)), "f"(nz(v.w)) : "memory");
}
__device__ __forceinline__ void stx2(float* p, float a, float b) {
  asm volatile("st.relaxed.gpu.global.v2.f32 [%0], {%1,%2};" ::"l"(p), "f"(nz(a)), "f"(nz(b)) : "memory");
}
__device__ __forceinline__ void stx1(float* p, float a) {
  asm volatile("st.relaxed.gpu.global.f32 [%0], %1;" ::"l"(p), "f"(nz(a)) : "memory");
}
__device__ __forceinline__ void clr4(float* p) {
  asm volatile("st.relaxed.gpu.global.v4.f32 [%0], {%1,%1,%1,%1};" ::"l"(p), "f"(0.0f) : "memory");
}
__device__ __forceinline__ bool full4(const float4& v) {
  return __float_as_uint(v.x) != 0u && __float_as_uint(v.y) != 0u && __float_as_uint(v.z) != 0u && __float_as_uint(v.w) != 0u;
}
__device__ __forceinline__ void gather18(float4 (&v)[18], const float* po, const float* pml) {
#pragma unroll
  for (int k = 0; k < 18; k++) v[k] = ldx4(k < 16 ? po + k * 1024 : pml + (k - 16) * 128);
  for (int it = 0;; it++) {
    bool ok = true;
#pragma unroll
    for (int k = 0; k < 18; k++) ok = ok && full4(v[k]);
    if (__all_sync(0xffffffffu, ok)) break;
    if (it > kSpinLimit) __trap();
    __nanosleep(40);
#pragma unroll
    for (int k = 0; k < 18; k++)
      if (!full4(v[k])) v[k] = ldx4(k < 16 ? po + k * 1024 : pml + (k - 16) * 128);
  }
}

__device__ __forceinline__ void load_wo(uint32_t (&a)[18][4], uint32_t base, int w, int lane) {
  const uint32_t wl = ((lane & 7) + (lane >> 4) * 8) * 128 + ((((lane >> 3) & 1) ^ (lane & 7)) << 4);
#pragma unroll
  for (int mt = 0; mt < 9; mt++) {
    const int tile = w * 9 + mt;
    const uint32_t ad = base + (tile >> 2) * 4096 + (wl ^ ((tile & 3) << 5));
    ldsm4t(a[2 * mt], ad);
    ldsm4t(a[2 * mt + 1], ad + 2048);
  }
}

struct Maps {
  CUtensorMap wg, wu, wd, k, v, wo;
};

__global__ void __launch_bounds__(kThreads, 1)
fused_decode_kernel(const char* __restrict__ wqp, const __nv_bfloat16* __restrict__ x,
                    __nv_bfloat16* __restrict__ out, Scratch* sc, const __grid_constant__ Maps maps) {
  if (threadIdx.x == 224 && blockIdx.x < kSliceCtas)
    asm volatile("cp.async.bulk.prefetch.L2.global [%0], %1;" ::"l"(wqp + (size_t)blockIdx.x * 36864), "r"(36864) : "memory");
  extern __shared__ unsigned char smem_dyn[];
  unsigned char* sm = smem_dyn + ((1024u - (smem_u32(smem_dyn) & 1023u)) & 1023u);
  const uint32_t sb = smem_u32(sm);
  const int tid = threadIdx.x, warp = tid >> 5, lane = tid & 31;
  const int cta = blockIdx.x, G = gridDim.x;
  const uint32_t barFull = sb + kOffBar, barEmpty = barFull + kSlots * 8, barInfo = barEmpty + kSlots * 8;
  const uint32_t barMfull = barInfo + kSlots * 8, barMempty = barMfull + 16;
  const uint32_t barWo = barMempty + 16, barD = barWo + 8, barQ = barD + 8, barQok = barQ + 8;
  const uint32_t barFree = barQok + 8;
  volatile int* info = reinterpret_cast<volatile int*>(sm + kOffInfo);
  constexpr int kLastBatch = kNAtt - kHKV * kItemsPerPair;

  uint2 xr[9];
  if (warp < 4) {
    const uint2* xp = reinterpret_cast<const uint2*>(x + (warp * 2 + (lane >> 4)) * kD) + (lane & 15);
#pragma unroll
    for (int i = 0; i < 9; i++) xr[i] = __ldg(xp + i * 16);
    if (cta < kSliceCtas) {
      const uint32_t dst = sb + kOffW + warp * 9216 + (lane >> 2) * 64 + (((lane & 3) ^ ((lane >> 3) & 3)) << 4);
      const char* src = wqp + (size_t)(warp * 144 + (lane >> 2)) * 8192 + cta * 64 + (lane & 3) * 16;
#pragma unroll 1
      for (int i = 0; i < 18; i++) cp_async16(dst + i * 512, src + (size_t)i * 65536);
      asm volatile("cp.async.commit_group;" ::: "memory");
    }
  }
  if (warp == 5 && lane < 6)
    asm volatile("prefetch.tensormap [%0];" ::"l"(reinterpret_cast<const CUtensorMap*>(&maps) + lane) : "memory");
  unsigned nextDyn = 0;
  uint64_t pol = 0;
  if (tid == 128) {
    nextDyn = atom_add(&sc->ctr.claim, 1);
#pragma unroll
    for (int i = 0; i < kNumBars; i++) mbar_init(barFull + i * 8, ((kBarCount4 >> i) & 1) ? 4 : 1);
    asm volatile("fence.mbarrier_init.release.cluster;" ::: "memory");
    asm volatile("createpolicy.fractional.L2::evict_first.b64 %0, 1.0;" : "=l"(pol));
#pragma unroll 1
    for (int w = 0; w < kSlots; w++) {
      info[w] = cta;
      mbar_arrive(barInfo + w * 8);
      mbar_expect_tx(barFull + w * 8, 9216);
      tma2d(sb + kOffRing + w * kSlotBytes, &maps.wg + (w >> 2), cta * 32, (w & 3) * 144, barFull + w * 8, pol);
    }
  }
  __syncthreads();

  if (warp >= 4) {
  if (warp == 4) {
    if (lane == 0) {
      int item = cta, n = kSlots;
      while (true) {
        const int nsub = item < kNFfn ? 12 : 4;
#pragma unroll 1
        for (int w = item == cta ? kSlots : 0; w < nsub; w++, n++) {
          const int slot = n & (kSlots - 1);
          mbar_wait(barEmpty + slot * 8, ((n / kSlots) & 1) ^ 1);
          info[slot] = item;
          mbar_arrive(barInfo + slot * 8);
          const uint32_t fb = barFull + slot * 8;
          const uint32_t dst = sb + kOffRing + slot * kSlotBytes;
          if (item >= kNFfn) {
            if (item < kNItems) {
              mbar_expect_tx(fb, kSlotBytes);
              const int row = (item - kNFfn) * kItemRows + w * 32;
              tma3d(dst, &maps.k, 0, row, 0, fb, pol);
              tma3d(dst + 8192, &maps.v, 0, row, 0, fb, pol);
            }
          } else {
            mbar_expect_tx(fb, 9216);
            const int c = (w & 3) * 144;
            if (w < 8) tma2d(dst, w < 4 ? &maps.wg : &maps.wu, item * 32, c, fb, pol);
            else tma2d(dst, &maps.wd, c, item * 32, fb, pol);
          }
        }
        if (item >= kNItems) break;
        if (item + G < kNFfn) {
          item += G;
          continue;
        }
        item = (int)nextDyn + kNFfn;
        if (item < kNItems) nextDyn = atom_add(&sc->ctr.claim, 1);
      }
      if (cta < kSliceCtas) {
        mbar_wait(barFull + ((n - 5) & (kSlots - 1)) * 8, ((n - 5) / kSlots) & 1);
        mbar_expect_tx(barWo, 36864);
        tma4d(sb + kOffW, &maps.wo, 0, (cta & 7) * 16, (cta >> 3) * 2, 0, barWo, pol);
      }
    }
  } else if (warp == 5) {
    const float* mb = reinterpret_cast<const float*>(sm + kOffMbuf);
    int pend = -1;
    int batch = 0;
    if (lane == 0) {
      if (cta < kSliceCtas) {
        mbar_wait(barQ, 0);
        red_release(&sc->ctr.qready, 1);
      }
      poll_ge(&sc->ctr.qready, kSliceCtas, 50);
      mbar_arrive(barQok);
    }
    __syncwarp();
    for (int kk = 0;; kk++) {
      const int buf = kk & 1;
      mbar_wait(barMfull + buf * 8, (kk >> 1) & 1);
      const float* p = mb + buf * 4 * kMbufStride;
      const int item = __float_as_int(p[260]);
      if (pend >= 0 && lane == 0) red_release(&sc->ctr.done[pend * 32], 1);
      if (item < 0) break;
      if ((item >> 10) != batch) {
        batch = item >> 10;
        if (batch >= 2) mbar_wait(barFree + (batch - 2) * 8, 0);
      }
      float4 ml[4];
#pragma unroll
      for (int w = 0; w < 4; w++) ml[w] = *reinterpret_cast<const float4*>(p + w * kMbufStride + 256);
      const float M0 = fmaxf(fmaxf(ml[0].x, ml[1].x), fmaxf(ml[2].x, ml[3].x));
      const float M1 = fmaxf(fmaxf(ml[0].z, ml[1].z), fmaxf(ml[2].z, ml[3].z));
      float4 a = make_float4(0.f, 0.f, 0.f, 0.f), b = a;
      float L0 = 0.f, L1 = 0.f;
#pragma unroll
      for (int w = 0; w < 4; w++) {
        const float s0 = ex2(ml[w].x - M0), s1 = ex2(ml[w].z - M1);
        L0 = fmaf(s0, ml[w].y, L0);
        L1 = fmaf(s1, ml[w].w, L1);
        const float4 u = *reinterpret_cast<const float4*>(p + w * kMbufStride + lane * 4);
        const float4 v = *reinterpret_cast<const float4*>(p + w * kMbufStride + 128 + lane * 4);
        a.x = fmaf(s0, u.x, a.x); a.y = fmaf(s1, u.y, a.y); a.z = fmaf(s0, u.z, a.z); a.w = fmaf(s1, u.w, a.w);
        b.x = fmaf(s0, v.x, b.x); b.y = fmaf(s1, v.y, b.y); b.z = fmaf(s0, v.z, b.z); b.w = fmaf(s1, v.w, b.w);
      }
      float* dst = sc->po + (size_t)PSLOT(item >> 6) * (kItemsPerPair * 256) + (item & 63) * 256;
      stx4(dst + lane * 4, a);
      stx4(dst + 128 + lane * 4, b);
      if (lane < 8)
        stx4(reinterpret_cast<float*>(sc->pml + (PSLOT(item >> 6) * 8 + lane) * kItemsPerPair + (item & 63)), make_float4(M0, L0, M1, L1));
      __syncwarp();
      pend = item >> 6;
      if (lane == 0) mbar_arrive(barMempty + buf * 8);
      if (item >= kLastBatch) pend = -1;
    }
  } else {
    const int cw = warp - 6;
    const int ci64 = tid - 192;
    mbar_wait(barQok, 0);
    if (ci64 == 0) {
      mbar_wait(barD, 0);
      red_release(&sc->ctr.ddone, 1);
    }
    if (cta < kSliceCtas) {
      if (lane == 0) poll_ge(&sc->ctr.ddone, G, 500);
      __syncwarp();
      float* ssum = reinterpret_cast<float*>(sm + kOffSsum);
      if (ci64 < 63) {
        const int q = ci64 % 9, pg = ci64 / 9;
        float4 acc = make_float4(0.f, 0.f, 0.f, 0.f);
#pragma unroll 4
        for (int p = pg; p < G; p += 7) {
          const float4 v = ldx4(sc->dp + p * kOutElems + cta * 36 + q * 4);
          acc.x += v.x; acc.y += v.y; acc.z += v.z; acc.w += v.w;
        }
        *reinterpret_cast<float4*>(ssum + pg * 36 + q * 4) = acc;
      }
      float* g7 = reinterpret_cast<float*>(sm + kOffG7);
      if (cta < kRow7Ctas) {
        float acc = 0.f;
#pragma unroll 4
        for (int p = ci64 >> 3; p < G; p += 8) acc += __ldcg(sc->dp + p * kOutElems + (cta * 8 + (ci64 & 7)) * 8 + 7);
        g7[ci64] = acc;
      }
      bar_sync(2, 64);
      if (cta < kRow7Ctas && ci64 >= 56) {
        float d = 0.f;
#pragma unroll
        for (int k = 0; k < 8; k++) d += g7[k * 8 + (ci64 & 7)];
        g7[64 + (ci64 & 7)] = bf16r(silu_f(bf16r(d)));
      }
      if (ci64 < 36) {
        float d = 0.f;
#pragma unroll
        for (int k = 0; k < 7; k++) d += ssum[k * 36 + ci64];
        ssum[252 + ci64] = bf16r(silu_f(bf16r(d)));
      }
      const int kvh = cta >> 3, sl = cta & 7;
      float2* wbuf = reinterpret_cast<float2*>(sm + kOffWbuf) + cw * 64;
      __nv_bfloat16* os = reinterpret_cast<__nv_bfloat16*>(sm + kOffOs);
      const int ci = lane >> 3, q4 = lane & 7;
#pragma unroll 1
      for (int b = cw; b < kB; b += 2) {
        const int pair = b * kHKV + kvh;
        if (b == 4 + cw) {
#pragma unroll 2
          for (int k = 0; k < 18; k++) clr4(sc->sp + cta * kOutElems + (k * 64 + ci64) * 4);
          const int pair7 = PSLOT(7 * kHKV + kvh);
#pragma unroll 2
          for (int k = 0; k < 8; k++)
            clr4(sc->po + ((size_t)pair7 * kItemsPerPair + k * 8 + (ci64 >> 3)) * 256 + sl * 32 + (ci64 & 7) * 4);
          clr4(reinterpret_cast<float*>(sc->pml + (pair7 * 8 + sl) * kItemsPerPair + ci64));
          if (cta < kRow7Ctas) {
#pragma unroll
            for (int k = 0; k < 4; k++) clr4(sc->s7 + cta * 1024 + (k * 64 + ci64) * 4);
          }
          __syncwarp();
          if (lane == 0) red_release(&sc->ctr.zready, 1);
        }
        if (b >= 2 && lane == 0) {
          if (b == 7) poll_ge(&sc->ctr.zready, kSliceCtas * 2, 200);
          else poll_ge(&sc->ctr.cons[(b - 2) * 32], kSliceCtas, 200);
          mbar_arrive(barFree + (b - 2) * 8);
        }
        if (b == 7) break;
        const float* pml = reinterpret_cast<const float*>(sc->pml + (PSLOT(pair) * 8 + sl) * kItemsPerPair);
        if (lane == 0) poll_ge(&sc->ctr.done[pair * 32], kItemsPerPair, 300);
        __syncwarp();
        const float* po = sc->po + (size_t)PSLOT(pair) * kItemsPerPair * 256 + sl * 32 + q4 * 4 + ci * 256;
        float4 v[18];
        gather18(v, po, pml + lane * 4);
        __syncwarp();
        if (lane == 0 && b < 5) red_release(&sc->ctr.cons[b * 32], 1);
        const float4 mlA = v[16], mlB = v[17];
        const float M0 = warp_max(fmaxf(mlA.x, mlB.x)), M1 = warp_max(fmaxf(mlA.z, mlB.z));
        const float wA0 = ex2(mlA.x - M0), wA1 = ex2(mlA.z - M1), wB0 = ex2(mlB.x - M0), wB1 = ex2(mlB.z - M1);
        float L0 = wA0 * mlA.y + wB0 * mlB.y, L1 = wA1 * mlA.w + wB1 * mlB.w;
        wbuf[lane] = make_float2(wA0, wA1);
        wbuf[32 + lane] = make_float2(wB0, wB1);
        __syncwarp();
        float4 acc = make_float4(0.f, 0.f, 0.f, 0.f);
#pragma unroll
        for (int k = 0; k < 16; k++) {
          const float2 w2 = wbuf[k * 4 + ci];
          acc.x = fmaf(w2.x, v[k].x, acc.x); acc.y = fmaf(w2.y, v[k].y, acc.y);
          acc.z = fmaf(w2.x, v[k].z, acc.z); acc.w = fmaf(w2.y, v[k].w, acc.w);
        }
#pragma unroll
        for (int o = 1; o <= 16; o <<= 1) {
          L0 += __shfl_xor_sync(0xffffffffu, L0, o);
          L1 += __shfl_xor_sync(0xffffffffu, L1, o);
          if (o >= 8) {
            acc.x += __shfl_xor_sync(0xffffffffu, acc.x, o); acc.y += __shfl_xor_sync(0xffffffffu, acc.y, o);
            acc.z += __shfl_xor_sync(0xffffffffu, acc.z, o); acc.w += __shfl_xor_sync(0xffffffffu, acc.w, o);
          }
        }
        if (lane < 8) {
          const float r0 = 1.0f / L0, r1 = 1.0f / L1;
          *reinterpret_cast<uint32_t*>(os + b * 40 + q4 * 2) = pack_bf16(acc.x * r0, acc.z * r0);
          *reinterpret_cast<uint32_t*>(os + b * 40 + 16 + q4 * 2) = pack_bf16(acc.y * r1, acc.w * r1);
        }
        __syncwarp();
      }
      __syncwarp();
      if (cta < kRow7Ctas) bar_arrive(4, 192);
    } else if (lane == 0) {
      for (int b = 2 + cw; b < kB; b += 2) {
        if (b == 7) poll_ge(&sc->ctr.zready, kSliceCtas * 2, 500);
        else poll_ge(&sc->ctr.cons[(b - 2) * 32], kSliceCtas, 500);
        mbar_arrive(barFree + (b - 2) * 8);
      }
    }
  }
    __syncwarp();
    if (cta < kSliceCtas) {
      const int aw = warp - 4, at = tid - 128;
      const int g = lane >> 2, t = lane & 3;
      const int oe = cta * 36 + at;
      float xv = 0.f;
      if (at < 36) xv = __bfloat162float(x[(oe & 7) * kD + (oe >> 3)]);
      mbar_wait(barFree + 5 * 8, 0);
      mbar_wait(barWo, 0);
      uint32_t a[18][4];
      load_wo(a, sb + kOffW, aw, lane);
      bar_sync(3, 128);
      uint32_t ob[4] = {0u, 0u, 0u, 0u};
      if (g < 7) {
        const __nv_bfloat16* os = reinterpret_cast<const __nv_bfloat16*>(sm + kOffOs) + g * 40 + t * 2;
#pragma unroll
        for (int j = 0; j < 4; j++) ob[j] = *reinterpret_cast<const uint32_t*>(os + j * 8);
      }
#pragma unroll
      for (int mt = 0; mt < 9; mt++) {
        float c[4] = {0.f, 0.f, 0.f, 0.f};
        mma16816(c, a[2 * mt], ob[0], ob[1]);
        mma16816(c, a[2 * mt + 1], ob[2], ob[3]);
#pragma unroll
        for (int h = 0; h < 2; h++) {
          const int e = ((mt * 2 + h) * 8 + g) * 8 + t * 2, u = e / 36;
          stx2(sc->sp + ((aw * 32 + u) * kSliceCtas + cta) * 36 + (e - u * 36), c[2 * h], c[2 * h + 1]);
        }
      }
      bar_sync(5, 256);
      const float* fp = sc->sp + cta * kOutElems + at * 4;
      const int fcnt = at < 18 ? 10 : (at < 126 ? 9 : 0);
      float4 f[10];
#pragma unroll
      for (int k = 0; k < 10; k++) f[k] = k < fcnt ? ldx4(fp + k * 504) : make_float4(-0.f, -0.f, -0.f, -0.f);
      for (int it = 0;; it++) {
        bool ok = true;
#pragma unroll
        for (int k = 0; k < 10; k++) ok = ok && full4(f[k]);
        if (__all_sync(0xffffffffu, ok)) break;
        if (it > kSpinLimit) __trap();
        __nanosleep(40);
#pragma unroll
        for (int k = 0; k < 10; k++)
          if (!full4(f[k])) f[k] = ldx4(fp + k * 504);
      }
      float* fsum = reinterpret_cast<float*>(sm + kOffFsum);
      float4 acc = f[0];
#pragma unroll
      for (int k = 1; k < 10; k++) { acc.x += f[k].x; acc.y += f[k].y; acc.z += f[k].z; acc.w += f[k].w; }
      if (at < 126) *reinterpret_cast<float4*>(fsum + at * 4) = acc;
      bar_sync(3, 128);
      if (at < 36 && (oe & 7) != 7) {
        float s = 0.f;
#pragma unroll
        for (int k = 0; k < 14; k++) s += fsum[k * 36 + at];
        const float gt = reinterpret_cast<const float*>(sm + kOffSsum)[252 + at];
        out[(oe & 7) * kD + (oe >> 3)] = __float2bfloat16_rn(xv + bf16r(bf16r(s) * gt));
      }
    }
  } else {
    const int g = lane >> 2, t = lane & 3;
    __nv_bfloat16* xn = reinterpret_cast<__nv_bfloat16*>(sm + kOffXn);
    {
      float v[36];
#pragma unroll
      for (int i = 0; i < 9; i++) {
        v[4 * i] = __uint_as_float(xr[i].x << 16);
        v[4 * i + 1] = __uint_as_float(xr[i].x & 0xffff0000u);
        v[4 * i + 2] = __uint_as_float(xr[i].y << 16);
        v[4 * i + 3] = __uint_as_float(xr[i].y & 0xffff0000u);
      }
      float s = 0.f;
#pragma unroll
      for (int i = 0; i < 36; i++) s += v[i];
#pragma unroll
      for (int o = 8; o > 0; o >>= 1) s += __shfl_xor_sync(0xffffffffu, s, o);
      const float mean = s * (1.0f / kD);
      float q = 0.f;
#pragma unroll
      for (int i = 0; i < 36; i++) { const float d = v[i] - mean; q = fmaf(d, d, q); }
#pragma unroll
      for (int o = 8; o > 0; o >>= 1) q += __shfl_xor_sync(0xffffffffu, q, o);
      const float mb = bf16r(mean);
      const float rden = 1.0f / bf16r(sqrtf(bf16r(bf16r(q * (1.0f / kD)) + 1e-5f)));
      __nv_bfloat16* xw = xn + (warp * 2 + (lane >> 4)) * kXnPitch + (lane & 15) * 4;
#pragma unroll
      for (int i = 0; i < 9; i++)
        *reinterpret_cast<uint2*>(xw + i * 64) =
            make_uint2(pack_bf16(bf16r(v[4 * i] - mb) * rden, bf16r(v[4 * i + 1] - mb) * rden),
                       pack_bf16(bf16r(v[4 * i + 2] - mb) * rden, bf16r(v[4 * i + 3] - mb) * rden));
    }
    bar_sync(1, 128);
    float* mb = reinterpret_cast<float*>(sm + kOffMbuf);
    const uint32_t r8 = lane & 7;
    const uint32_t guLane = (r8 + (lane >> 4) * 8) * 64 + ((((lane >> 3) & 1) ^ (r8 >> 1)) << 4);
    int slot = warp, item;
    uint32_t fph = 0;
    {
      uint32_t xb[9][2];
#pragma unroll
      for (int ks = 0; ks < 9; ks++) {
        xb[ks][0] = *reinterpret_cast<const uint32_t*>(xn + g * kXnPitch + warp * 144 + ks * 16 + t * 2);
        xb[ks][1] = *reinterpret_cast<const uint32_t*>(xn + g * kXnPitch + warp * 144 + ks * 16 + 8 + t * 2);
      }
      if (cta < kSliceCtas) {
        if (tid == 0) {
          sc->ctr.done[cta * 32] = 0;
          if (cta < 8) sc->ctr.cons[cta * 32] = 0;
          if (cta == 0) { sc->ctr.ddone = 0; sc->ctr.zready = 0; sc->ctr.exitc = 0; }
        }
        asm volatile("cp.async.wait_group 0;" ::: "memory");
        __syncwarp();
        const uint32_t lo = sb + kOffW + warp * 9216;
        uint32_t a[18][4];
#pragma unroll
        for (int i = 0; i < 18; i++) ldsm4t(a[i], lo + (guLane ^ ((i & 1) * 32)) + (i >> 1) * 1024);
        float c[2][4] = {{0.f, 0.f, 0.f, 0.f}, {0.f, 0.f, 0.f, 0.f}};
#pragma unroll
        for (int i = 0; i < 18; i++) mma16816(c[i & 1], a[i], xb[i >> 1][0], xb[i >> 1][1]);
        float* qr = mb + warp * 256;
#pragma unroll
        for (int mt = 0; mt < 2; mt++) {
          *reinterpret_cast<float2*>(qr + (mt * 16 + g) * 8 + t * 2) = make_float2(c[mt][0], c[mt][1]);
          *reinterpret_cast<float2*>(qr + (mt * 16 + 8 + g) * 8 + t * 2) = make_float2(c[mt][2], c[mt][3]);
        }
        bar_sync(1, 128);
        const int b = tid >> 4, cp = tid & 15;
        float q0 = 0.f, q1 = 0.f;
#pragma unroll
        for (int w = 0; w < 4; w++) {
          q0 += mb[w * 256 + (cp * 2) * 8 + b];
          q1 += mb[w * 256 + (cp * 2 + 1) * 8 + b];
        }
        const int col = cta * 32 + cp * 2;
        const int head = col >> 7, d = col & 127;
        const int pos = (head & 1) * 128 + (d >> 5) * 32 + ((d & 7) >> 1) * 8 + ((d >> 4) & 1) * 4 + ((d >> 3) & 1) * 2;
        *reinterpret_cast<uint32_t*>(sc->q + (b * kHKV + (head >> 1)) * 256 + pos) = pack_bf16(q0, q1);
        __syncwarp();
        if (lane == 0) mbar_arrive(barQ);
      } else {
        bar_sync(1, 128);
      }

      float dacc[9][4];
#pragma unroll
      for (int i = 0; i < 9; i++) dacc[i][0] = dacc[i][1] = dacc[i][2] = dacc[i][3] = 0.f;
      float* red = reinterpret_cast<float*>(sm + kOffXn);
      const uint32_t dnLane = (r8 + (lane >> 4) * 8) * 288 + ((lane >> 3) & 1) * 16;
      while (true) {
        mbar_wait(barInfo + slot * 8, fph);
        item = info[slot];
        if (item >= kNFfn) break;
        uint32_t a[18][4];
        float* rw = red + warp * 512;
#pragma unroll 1
        for (int gu = 0; gu < 2; gu++) {
          mbar_wait(barFull + slot * 8, fph);
          const uint32_t base = sb + kOffRing + slot * kSlotBytes;
#pragma unroll
          for (int i = 0; i < 18; i++) ldsm4t(a[i], base + (guLane ^ ((i & 1) * 32)) + (i >> 1) * 1024);
          float c[2][4] = {{0.f, 0.f, 0.f, 0.f}, {0.f, 0.f, 0.f, 0.f}};
#pragma unroll
          for (int i = 0; i < 18; i++) mma16816(c[i & 1], a[i], xb[i >> 1][0], xb[i >> 1][1]);
#pragma unroll
          for (int mt = 0; mt < 2; mt++) {
            float* r = rw + gu * 256 + (2 * t) * 32 + mt * 16 + g;
            r[0] = c[mt][0]; r[32] = c[mt][1]; r[8] = c[mt][2]; r[40] = c[mt][3];
          }
          __syncwarp();
          if (lane == 0) mbar_arrive(barEmpty + slot * 8);
          slot += 4;
          if (slot >= kSlots) { slot -= kSlots; fph ^= 1; }
        }
        bar_sync(1, 128);
        uint32_t hb[4];
#pragma unroll
        for (int j = 0; j < 4; j++) {
          float2 gs = make_float2(0.f, 0.f), us = gs;
#pragma unroll
          for (int w = 0; w < 4; w++) {
            const float* rr = red + w * 512 + g * 32 + j * 8 + t * 2;
            const float2 a2 = *reinterpret_cast<const float2*>(rr), b2 = *reinterpret_cast<const float2*>(rr + 256);
            gs.x += a2.x; gs.y += a2.y; us.x += b2.x; us.y += b2.y;
          }
          hb[j] = pack_bf16(bf16r(silu_f(bf16r(gs.x))) * bf16r(us.x), bf16r(silu_f(bf16r(gs.y))) * bf16r(us.y));
        }
        mbar_wait(barFull + slot * 8, fph);
        const uint32_t base = sb + kOffRing + slot * kSlotBytes + dnLane;
#pragma unroll
        for (int i = 0; i < 18; i++) ldsm4t(a[i], base + (i >> 1) * 32 + (i & 1) * 4608);
#pragma unroll
        for (int i = 0; i < 18; i++) mma16816(dacc[i >> 1], a[i], hb[(i & 1) * 2], hb[(i & 1) * 2 + 1]);
        bar_sync(1, 128);
        if (lane == 0) mbar_arrive(barEmpty + slot * 8);
        slot += 4;
        if (slot >= kSlots) { slot -= kSlots; fph ^= 1; }
      }
      float* dp = sc->dp + cta * kOutElems + (warp * 144 + g) * 8 + t * 2;
#pragma unroll
      for (int mt = 0; mt < 9; mt++) {
        *reinterpret_cast<float2*>(dp + mt * 128) = make_float2(dacc[mt][0], dacc[mt][1]);
        *reinterpret_cast<float2*>(dp + mt * 128 + 64) = make_float2(dacc[mt][2], dacc[mt][3]);
      }
      __syncwarp();
      if (lane == 0) mbar_arrive(barD);
      mbar_wait(barQok, 0);
    }

    const float kScale = 0.08838834764831845f * 1.4426950408889634f;
    const uint32_t kLane = (r8 + ((lane >> 3) & 1) * 8) * 128 + (((lane >> 4) ^ r8) << 4);
    const uint32_t vLane = 8192 + (r8 + (lane >> 4) * 8) * 128 + ((((lane >> 3) & 1) ^ r8) << 4);
    int kk = 0;
    while (item < kNItems) {
      item -= kNFfn;
      uint4 qv[4];
      if (g < 2) {
        const uint4* qs = reinterpret_cast<const uint4*>(sc->q + (item >> 6) * 256 + g * 128 + t * 8);
#pragma unroll
        for (int i = 0; i < 4; i++) qv[i] = qs[i * 4];
      } else {
#pragma unroll
        for (int i = 0; i < 4; i++) qv[i] = make_uint4(0u, 0u, 0u, 0u);
      }
      mbar_wait(barFull + slot * 8, fph);
      const uint32_t base = sb + kOffRing + slot * kSlotBytes;
      uint32_t ka[16][4], va[16][4];
#pragma unroll
      for (int i = 0; i < 16; i++)
        ldsm4(ka[i], base + ((kLane ^ (((i >> 1) & 3) << 5)) + (i >> 3) * 4096 + (i & 1) * 2048));
#pragma unroll
      for (int i = 0; i < 16; i++)
        ldsm4t(va[i], base + ((vLane ^ (((i >> 1) & 3) << 5)) + (i >> 3) * 4096 + (i & 1) * 2048));
      float s[2][4], s2[2][4];
#pragma unroll
      for (int i = 0; i < 4; i++) s[0][i] = s[1][i] = s2[0][i] = s2[1][i] = 0.f;
#pragma unroll
      for (int kp = 0; kp < 4; kp++) {
        mma16816(s[0], ka[4 * kp], qv[kp].x, qv[kp].y);
        mma16816(s[1], ka[4 * kp + 1], qv[kp].x, qv[kp].y);
        mma16816(s2[0], ka[4 * kp + 2], qv[kp].z, qv[kp].w);
        mma16816(s2[1], ka[4 * kp + 3], qv[kp].z, qv[kp].w);
      }
#pragma unroll
      for (int i = 0; i < 4; i++) { s[0][i] += s2[0][i]; s[1][i] += s2[1][i]; }
      float m0 = fmaxf(fmaxf(s[0][0], s[0][2]), fmaxf(s[1][0], s[1][2]));
      float m1 = fmaxf(fmaxf(s[0][1], s[0][3]), fmaxf(s[1][1], s[1][3]));
#pragma unroll
      for (int o = 4; o <= 16; o <<= 1) {
        m0 = fmaxf(m0, __shfl_xor_sync(0xffffffffu, m0, o));
        m1 = fmaxf(m1, __shfl_xor_sync(0xffffffffu, m1, o));
      }
      m0 *= kScale; m1 *= kScale;
      float l0 = 0.f, l1 = 0.f;
      uint32_t pb[2][2];
#pragma unroll
      for (int mt = 0; mt < 2; mt++) {
        const float p0 = ex2(fmaf(s[mt][0], kScale, -m0)), p1 = ex2(fmaf(s[mt][1], kScale, -m1));
        const float p2 = ex2(fmaf(s[mt][2], kScale, -m0)), p3 = ex2(fmaf(s[mt][3], kScale, -m1));
        l0 += p0 + p2; l1 += p1 + p3;
        pb[mt][0] = movmat(pack_bf16(p0, p1));
        pb[mt][1] = movmat(pack_bf16(p2, p3));
      }
      float o_[8][4];
#pragma unroll
      for (int j = 0; j < 8; j++) {
        o_[j][0] = o_[j][1] = o_[j][2] = o_[j][3] = 0.f;
        mma16816(o_[j], va[2 * j], pb[0][0], pb[0][1]);
      }
#pragma unroll
      for (int j = 0; j < 8; j++) mma16816(o_[j], va[2 * j + 1], pb[1][0], pb[1][1]);
#pragma unroll
      for (int o = 4; o <= 16; o <<= 1) {
        l0 += __shfl_xor_sync(0xffffffffu, l0, o);
        l1 += __shfl_xor_sync(0xffffffffu, l1, o);
      }
      const int buf = kk & 1;
      mbar_wait(barMempty + buf * 8, ((kk >> 1) & 1) ^ 1);
      float* p = mb + (buf * 4 + warp) * kMbufStride;
      if (t == 0) {
#pragma unroll
        for (int j = 0; j < 8; j++) {
          *reinterpret_cast<float2*>(p + (j * 16 + g) * 2) = make_float2(o_[j][0], o_[j][1]);
          *reinterpret_cast<float2*>(p + (j * 16 + 8 + g) * 2) = make_float2(o_[j][2], o_[j][3]);
        }
        if (g == 0) {
          *reinterpret_cast<float4*>(p + 256) = make_float4(m0, l0, m1, l1);
          p[260] = __int_as_float(item);
        }
      }
      __syncwarp();
      if (lane == 0) {
        mbar_arrive(barMfull + buf * 8);
        mbar_arrive(barEmpty + slot * 8);
      }
      kk++;
      slot += 4;
      if (slot >= kSlots) { slot -= kSlots; fph ^= 1; }
      mbar_wait(barInfo + slot * 8, fph);
      item = info[slot];
    }
    {
      const int buf = kk & 1;
      mbar_wait(barMempty + buf * 8, ((kk >> 1) & 1) ^ 1);
      if (lane == 0) {
        mb[(buf * 4 + warp) * kMbufStride + 260] = __int_as_float(-1);
        mbar_arrive(barMfull + buf * 8);
        if (warp == 0) red_relaxed(&sc->ctr.exitc, 1);
      }
      __syncwarp();
    }
    if (cta < kSliceCtas) {
      float xv = 0.f;
      if (tid < 8 && cta < kRow7Ctas) xv = __bfloat162float(x[7 * kD + cta * 8 + tid]);
      mbar_wait(barFree + 5 * 8, 0);
      const int ps = PSLOT(7 * kHKV + (cta >> 3)), sl = cta & 7;
      const int ci = lane >> 3, q4 = lane & 7;
      const float* po = sc->po + (ps * kItemsPerPair + warp * 16 + ci) * 256 + sl * 32 + q4 * 4;
      const float* pml = reinterpret_cast<const float*>(sc->pml + (ps * 8 + sl) * kItemsPerPair + warp * 16 + (lane & 15));
      float4 v[5];
#pragma unroll
      for (int k = 0; k < 5; k++) v[k] = ldx4(k < 4 ? po + k * 1024 : pml);
      uint32_t a[18][4], ob[4];
      bool haveWo = false;
      for (int it = 0;; it++) {
        if (!haveWo && __all_sync(0xffffffffu, mbar_test(barWo, 0))) {
          load_wo(a, sb + kOffW, warp, lane);
          haveWo = true;
        }
        bool ok = true;
#pragma unroll
        for (int k = 0; k < 5; k++) ok = ok && full4(v[k]);
        if (__all_sync(0xffffffffu, ok) && haveWo) break;
        if (it > kSpinLimit) __trap();
#pragma unroll
        for (int k = 0; k < 5; k++)
          if (!full4(v[k])) v[k] = ldx4(k < 4 ? po + k * 1024 : pml);
      }
      float* cb = reinterpret_cast<float*>(sm + kOffCbuf);
      {
        const float M0 = warp_max(v[4].x), M1 = warp_max(v[4].z);
        const float w0 = ex2(v[4].x - M0), w1 = ex2(v[4].z - M1);
        float L0 = w0 * v[4].y, L1 = w1 * v[4].w;
        float4 acc = make_float4(0.f, 0.f, 0.f, 0.f);
#pragma unroll
        for (int k = 0; k < 4; k++) {
          const float a0 = __shfl_sync(0xffffffffu, w0, k * 4 + ci), a1 = __shfl_sync(0xffffffffu, w1, k * 4 + ci);
          acc.x = fmaf(a0, v[k].x, acc.x); acc.y = fmaf(a1, v[k].y, acc.y);
          acc.z = fmaf(a0, v[k].z, acc.z); acc.w = fmaf(a1, v[k].w, acc.w);
        }
#pragma unroll
        for (int o = 1; o <= 16; o <<= 1) {
          if (o <= 8) {
            L0 += __shfl_xor_sync(0xffffffffu, L0, o);
            L1 += __shfl_xor_sync(0xffffffffu, L1, o);
          }
          if (o >= 8) {
            acc.x += __shfl_xor_sync(0xffffffffu, acc.x, o); acc.y += __shfl_xor_sync(0xffffffffu, acc.y, o);
            acc.z += __shfl_xor_sync(0xffffffffu, acc.z, o); acc.w += __shfl_xor_sync(0xffffffffu, acc.w, o);
          }
        }
        if (lane < 8) {
          *reinterpret_cast<float2*>(cb + warp * 40 + q4 * 2) = make_float2(acc.x, acc.z);
          *reinterpret_cast<float2*>(cb + warp * 40 + 16 + q4 * 2) = make_float2(acc.y, acc.w);
          if (lane == 0) *reinterpret_cast<float4*>(cb + warp * 40 + 32) = make_float4(M0, L0, M1, L1);
        }
      }
      bar_sync(1, 128);
      {
        float4 ml[4];
#pragma unroll
        for (int w = 0; w < 4; w++) ml[w] = *reinterpret_cast<const float4*>(cb + w * 40 + 32);
        const float M0 = fmaxf(fmaxf(ml[0].x, ml[1].x), fmaxf(ml[2].x, ml[3].x));
        const float M1 = fmaxf(fmaxf(ml[0].z, ml[1].z), fmaxf(ml[2].z, ml[3].z));
        float L0 = 0.f, L1 = 0.f;
        float2 o2[4] = {{0.f, 0.f}, {0.f, 0.f}, {0.f, 0.f}, {0.f, 0.f}};
#pragma unroll
        for (int w = 0; w < 4; w++) {
          const float s0 = ex2(ml[w].x - M0), s1 = ex2(ml[w].z - M1);
          L0 = fmaf(s0, ml[w].y, L0);
          L1 = fmaf(s1, ml[w].w, L1);
#pragma unroll
          for (int j = 0; j < 4; j++) {
            const float2 u = *reinterpret_cast<const float2*>(cb + w * 40 + j * 8 + t * 2);
            o2[j].x = fmaf(j < 2 ? s0 : s1, u.x, o2[j].x);
            o2[j].y = fmaf(j < 2 ? s0 : s1, u.y, o2[j].y);
          }
        }
        const float r0 = __frcp_rn(L0), r1 = __frcp_rn(L1);
#pragma unroll
        for (int j = 0; j < 4; j++) ob[j] = pack_bf16(o2[j].x * (j < 2 ? r0 : r1), o2[j].y * (j < 2 ? r0 : r1));
      }
      {
        float c[10][4];
#pragma unroll
        for (int mt = 0; mt < 9; mt++) {
          c[mt][0] = c[mt][1] = c[mt][2] = c[mt][3] = 0.f;
          mma16816(c[mt], a[2 * mt], ob[0], ob[1]);
          mma16816(c[mt], a[2 * mt + 1], ob[2], ob[3]);
        }
        c[9][0] = c[9][2] = 0.f;
        float* s7 = sc->s7 + ((warp * 18 + t) * kSliceCtas + cta) * 8 + g;
#pragma unroll
        for (int k = 0; k < 5; k++) {
          const float lo = (t & 1) ? c[2 * k][2] : c[2 * k][0], hi = (t & 1) ? c[2 * k + 1][2] : c[2 * k + 1][0];
          if (k < 4 || t < 2) stx1(s7 + k * 4 * kSliceCtas * 8, (t & 2) ? hi : lo);
        }
      }
      bar_arrive(5, 256);
      if (cta < kRow7Ctas) {
        const float* hp = sc->s7 + cta * 1024 + tid * 4;
        float4 f0 = ldx4(hp), f1 = ldx4(hp + 512);
        for (int it = 0; !__all_sync(0xffffffffu, full4(f0) && full4(f1)); it++) {
          if (it > kSpinLimit) __trap();
          if (!full4(f0)) f0 = ldx4(hp);
          if (!full4(f1)) f1 = ldx4(hp + 512);
        }
        float* g7 = reinterpret_cast<float*>(sm + kOffG7);
        float4 h = make_float4(f0.x + f1.x, f0.y + f1.y, f0.z + f1.z, f0.w + f1.w);
#pragma unroll
        for (int o = 2; o <= 16; o <<= 1) {
          h.x += __shfl_xor_sync(0xffffffffu, h.x, o); h.y += __shfl_xor_sync(0xffffffffu, h.y, o);
          h.z += __shfl_xor_sync(0xffffffffu, h.z, o); h.w += __shfl_xor_sync(0xffffffffu, h.w, o);
        }
        if (lane < 2) *reinterpret_cast<float4*>(g7 + 72 + warp * 8 + lane * 4) = h;
        bar_sync(4, 192);
        if (tid < 8) {
          const float s = (g7[72 + tid] + g7[80 + tid]) + (g7[88 + tid] + g7[96 + tid]);
          out[7 * kD + cta * 8 + tid] = __float2bfloat16_rn(xv + bf16r(bf16r(s) * g7[64 + tid]));
        }
      }
      if (cta == 0 && tid == 96) {
        poll_ge(&sc->ctr.exitc, G, 20);
        sc->ctr.claim = 0;
        sc->ctr.qready = 0;
      }
    }
  }
}

__global__ void fb_ln(const __nv_bfloat16* x, float* xn) {
  const int lane = threadIdx.x;
  const __nv_bfloat16* xr = x + blockIdx.x * kD;
  float s = 0.f, q = 0.f;
  for (int i = lane; i < kD; i += 32) s += __bfloat162float(xr[i]);
  for (int o = 16; o > 0; o >>= 1) s += __shfl_xor_sync(0xffffffffu, s, o);
  const float mean = s * (1.0f / kD);
  for (int i = lane; i < kD; i += 32) { const float d = __bfloat162float(xr[i]) - mean; q = fmaf(d, d, q); }
  for (int o = 16; o > 0; o >>= 1) q += __shfl_xor_sync(0xffffffffu, q, o);
  const float den = bf16r(sqrtf(bf16r(bf16r(q * (1.0f / kD)) + 1e-5f)));
  for (int i = lane; i < kD; i += 32) xn[blockIdx.x * kD + i] = bf16r(bf16r(__bfloat162float(xr[i]) - bf16r(mean)) / den);
}
__global__ void fb_gemv(const float* a, const float* a2, const __nv_bfloat16* w, float* o, int K, int N) {
  const int n = blockIdx.x * 64 + threadIdx.x, b = blockIdx.y;
  float s = 0.f;
  for (int k = 0; k < K; k++) {
    const float v = a2 ? bf16r(bf16r(silu_f(a[b * K + k])) * a2[b * K + k]) : a[b * K + k];
    s = fmaf(v, __bfloat162float(w[(size_t)k * N + n]), s);
  }
  o[b * N + n] = bf16r(s);
}
__global__ void fb_att(const float* q, const __nv_bfloat16* kc, const __nv_bfloat16* vc, float* o) {
  __shared__ float sm_[8][132];
  const int warp = threadIdx.x >> 5, lane = threadIdx.x & 31;
  const size_t base = (size_t)(blockIdx.x >> 1) * kSK * 128 + lane * 4;
  float qv[4], acc[4] = {0.f, 0.f, 0.f, 0.f}, m = -INFINITY, l = 0.f;
  for (int i = 0; i < 4; i++) qv[i] = q[blockIdx.x * 128 + lane * 4 + i];
  for (int j = warp; j < kSK; j += 8) {
    float s = 0.f;
    for (int i = 0; i < 4; i++) s = fmaf(qv[i], __bfloat162float(kc[base + (size_t)j * 128 + i]), s);
    for (int x = 16; x > 0; x >>= 1) s += __shfl_xor_sync(0xffffffffu, s, x);
    s *= 0.08838834764831845f;
    const float mn = fmaxf(m, s), c = __expf(m - mn), pr = __expf(s - mn);
    l = l * c + pr;
    for (int i = 0; i < 4; i++) acc[i] = acc[i] * c + pr * __bfloat162float(vc[base + (size_t)j * 128 + i]);
    m = mn;
  }
  for (int i = 0; i < 4; i++) sm_[warp][lane * 4 + i] = acc[i];
  if (lane == 0) { sm_[warp][128] = m; sm_[warp][129] = l; }
  __syncthreads();
  if (threadIdx.x < 128) {
    float M = -INFINITY, L = 0.f, r = 0.f;
    for (int w = 0; w < 8; w++) M = fmaxf(M, sm_[w][128]);
    for (int w = 0; w < 8; w++) { const float c = __expf(sm_[w][128] - M); L += c * sm_[w][129]; r += c * sm_[w][threadIdx.x]; }
    o[blockIdx.x * 128 + threadIdx.x] = bf16r(r / L);
  }
}
__global__ void fb_out(const __nv_bfloat16* x, const float* s, const float* d, __nv_bfloat16* out) {
  const int i = blockIdx.x * 64 + threadIdx.x;
  out[i] = __float2bfloat16_rn(__bfloat162float(x[i]) + bf16r(s[i] * bf16r(silu_f(d[i]))));
}

typedef CUresult (*EncodeFn)(CUtensorMap*, CUtensorMapDataType, cuuint32_t, void*, const cuuint64_t*,
                             const cuuint64_t*, const cuuint32_t*, const cuuint32_t*, CUtensorMapInterleave,
                             CUtensorMapSwizzle, CUtensorMapL2promotion, CUtensorMapFloatOOBfill);

void encode(EncodeFn fn, CUtensorMap* m, const void* base, int rank, const cuuint64_t* dims, const cuuint64_t* strides,
            const cuuint32_t* box, CUtensorMapSwizzle sw,
            CUtensorMapL2promotion promo = CU_TENSOR_MAP_L2_PROMOTION_L2_128B) {
  const cuuint32_t es[4] = {1, 1, 1, 1};
  fn(m, CU_TENSOR_MAP_DATA_TYPE_BFLOAT16, rank, const_cast<void*>(base), dims, strides, box, es,
     CU_TENSOR_MAP_INTERLEAVE_NONE, sw, promo, CU_TENSOR_MAP_FLOAT_OOB_FILL_NONE);
}

}

extern "C" void kernel_launch(void* const* d_in, const int* in_sizes, int n_in, void* d_out, int out_size) {
  (void)in_sizes; (void)n_in; (void)out_size;
  static EncodeFn fn = nullptr;
  static int sms = 0;
  static Scratch* sc = nullptr;
  if (!sms) {
    void* p = nullptr;
    cudaDriverEntryPointQueryResult qr;
    cudaGetDriverEntryPoint("cuTensorMapEncodeTiled", &p, cudaEnableDefault, &qr);
    fn = (EncodeFn)p;
    int dev = 0;
    cudaGetDevice(&dev);
    cudaDeviceGetAttribute(&sms, cudaDevAttrMultiProcessorCount, dev);
    cudaGetSymbolAddress(&p, g_raw);
    sc = reinterpret_cast<Scratch*>((reinterpret_cast<uintptr_t>(p) + (2u << 20) - 1) & ~(uintptr_t)((2u << 20) - 1));
    cudaFuncSetAttribute(fused_decode_kernel, cudaFuncAttributeMaxDynamicSharedMemorySize, kSmemBytes);
  }
  if (sms < kSliceCtas || !fn) {
    typedef const __nv_bfloat16* P;
    float* t = reinterpret_cast<float*>(sc);
    float *xn = t, *q = t + 8192, *o = q + 32768, *g = o + 32768, *u = g + 36864, *sv = u + 36864, *d = sv + 8192;
    fb_ln<<<kB, 32>>>((P)d_in[0], xn);
    fb_gemv<<<dim3(64, kB), 64>>>(xn, nullptr, (P)d_in[3], q, kD, 4096);
    fb_att<<<256, 256>>>(q, (P)d_in[1], (P)d_in[2], o);
    fb_gemv<<<dim3(9, kB), 64>>>(o, nullptr, (P)d_in[4], sv, 4096, kD);
    fb_gemv<<<dim3(72, kB), 64>>>(xn, nullptr, (P)d_in[6], g, kD, kF);
    fb_gemv<<<dim3(72, kB), 64>>>(xn, nullptr, (P)d_in[7], u, kD, kF);
    fb_gemv<<<dim3(9, kB), 64>>>(g, u, (P)d_in[8], d, kF, kD);
    fb_out<<<72, 64>>>((P)d_in[0], sv, d, (__nv_bfloat16*)d_out);
    return;
  }
  Maps maps;
  {
    const cuuint64_t dims[3] = {64, (cuuint64_t)kPairs * kSK, 2}, str[2] = {256, 128};
    const cuuint32_t box[3] = {64, 32, 2};
    encode(fn, &maps.k, d_in[1], 3, dims, str, box, CU_TENSOR_MAP_SWIZZLE_128B, CU_TENSOR_MAP_L2_PROMOTION_L2_256B);
    encode(fn, &maps.v, d_in[2], 3, dims, str, box, CU_TENSOR_MAP_SWIZZLE_128B, CU_TENSOR_MAP_L2_PROMOTION_L2_256B);
  }
  {
    const cuuint64_t dims[4] = {64, 128, 32, 9}, str[3] = {kD * 2, 128 * kD * 2, 128};
    const cuuint32_t box[4] = {64, 16, 2, 9};
    encode(fn, &maps.wo, d_in[4], 4, dims, str, box, CU_TENSOR_MAP_SWIZZLE_128B);
  }
  {
    const cuuint64_t dims[2] = {kF, kD}, str[1] = {kF * 2};
    const cuuint32_t box[2] = {32, 144};
    encode(fn, &maps.wg, d_in[6], 2, dims, str, box, CU_TENSOR_MAP_SWIZZLE_64B);
    encode(fn, &maps.wu, d_in[7], 2, dims, str, box, CU_TENSOR_MAP_SWIZZLE_64B);
  }
  {
    const cuuint64_t dims[2] = {kD, kF}, str[1] = {kD * 2};
    const cuuint32_t box[2] = {144, 32};
    encode(fn, &maps.wd, d_in[8], 2, dims, str, box, CU_TENSOR_MAP_SWIZZLE_NONE);
  }
  int grid = sms < kMaxCtas ? sms : kMaxCtas;
  fused_decode_kernel<<<grid, kThreads, kSmemBytes>>>((const char*)d_in[3], (const __nv_bfloat16*)d_in[0],
                                                      (__nv_bfloat16*)d_out, sc, maps);
}
```

```cpp
#include <cuda_runtime.h>
#include <cuda_bf16.h>
#include <cuda.h>
#include <stddef.h>
#include <stdint.h>

namespace {

constexpr int kB = 8, kD = 576, kHKV = 16, kSK = 8192, kF = 4608;
constexpr int kPairs = kB * kHKV;
constexpr int kItemRows = 128;
constexpr int kItemsPerPair = kSK / kItemRows;
constexpr int kNAtt = kPairs * kItemsPerPair;
constexpr int kNFfn = kF / 32;
constexpr int kNItems = kNAtt + kNFfn;
constexpr int kSlots = 8;
constexpr int kSlotBytes = 16384;
constexpr int kMaxCtas = kNFfn;
constexpr int kSliceCtas = 128;
constexpr int kRow7Ctas = 72;
constexpr int kThreads = 256;
constexpr int kOutElems = kB * kD;

constexpr int kOffRing = 0;
constexpr int kOffW = kOffRing + kSlots * kSlotBytes;
constexpr int kOffXn = kOffW + 36864;
constexpr int kXnPitch = 584;
constexpr int kOffMbuf = kOffXn + kB * kXnPitch * 2;
constexpr int kMbufStride = 264;
constexpr int kOffOs = kOffMbuf + 2 * 4 * kMbufStride * 4;
constexpr int kOffWbuf = kOffOs + 8 * 40 * 2;
constexpr int kOffFsum = kOffWbuf + 2 * 64 * 8;
constexpr int kOffSsum = kOffFsum + 14 * 36 * 4;
constexpr int kOffG7 = kOffSsum + 8 * 36 * 4;
constexpr int kOffCbuf = kOffG7 + 104 * 4;
constexpr int kOffInfo = kOffCbuf + 4 * 40 * 4;
constexpr int kOffBar = kOffInfo + 64;
constexpr int kNumBars = 3 * kSlots + 8 + 6;
constexpr unsigned long long kBarCount4 = 0x63ull << (3 * kSlots);
constexpr int kSmemBytes = kOffBar + kNumBars * 8 + 1024;
static_assert(kSmemBytes <= 232448, "smem");

constexpr int kPartSlots = 48;
__device__ __forceinline__ int PSLOT(int pair) { return pair >= 112 ? pair - 112 : 16 + (pair & 31); }

struct Counters {
  unsigned claim;
  unsigned qready; unsigned pad1[30];
  unsigned ddone;  unsigned pad2[31];
  unsigned zready; unsigned pad3[31];
  unsigned exitc;  unsigned pad4[31];
  unsigned cons[8 * 32];
  unsigned done[kPairs * 32];
};

struct Scratch {
  Counters ctr;
  alignas(128) __nv_bfloat16 q[kPairs * 256];
  alignas(128) float4 pml[kPartSlots * 8 * kItemsPerPair];
  alignas(128) float s7[kRow7Ctas * kSliceCtas * 8];
  alignas(128) float po[kPartSlots * kItemsPerPair * 256];
  alignas(128) float sp[kSliceCtas * kOutElems];
  alignas(128) float dp[kMaxCtas * kOutElems];
};
static_assert(offsetof(Scratch, po) + 16 * kItemsPerPair * 1024 <= (2u << 20), "batch-7 partials in the first page");
__device__ __align__(128) unsigned char g_raw[sizeof(Scratch) + (2u << 20)];

constexpr int kSpinLimit = 1 << 21;

__device__ __forceinline__ uint32_t smem_u32(const void* p) { return (uint32_t)__cvta_generic_to_shared(p); }
__device__ __forceinline__ void mbar_init(uint32_t bar, uint32_t cnt) {
  asm volatile("mbarrier.init.shared::cta.b64 [%0], %1;" ::"r"(bar), "r"(cnt) : "memory");
}
__device__ __forceinline__ void mbar_expect_tx(uint32_t bar, uint32_t bytes) {
  asm volatile("mbarrier.arrive.expect_tx.shared::cta.b64 _, [%0], %1;" ::"r"(bar), "r"(bytes) : "memory");
}
__device__ __forceinline__ void mbar_arrive(uint32_t bar) {
  asm volatile("mbarrier.arrive.shared::cta.b64 _, [%0];" ::"r"(bar) : "memory");
}
__device__ __forceinline__ void mbar_wait(uint32_t bar, uint32_t parity) {
  uint32_t done;
  int it = 0;
  do {
    asm volatile(
        "{\n.reg .pred p;\nmbarrier.try_wait.parity.shared::cta.b64 p, [%1], %2;\nselp.u32 %0, 1, 0, p;\n}"
        : "=r"(done) : "r"(bar), "r"(parity) : "memory");
    if (++it > kSpinLimit) __trap();
  } while (!done);
}
__device__ __forceinline__ bool mbar_test(uint32_t bar, uint32_t parity) {
  uint32_t done;
  asm volatile(
      "{\n.reg .pred p;\nmbarrier.test_wait.parity.shared::cta.b64 p, [%1], %2;\nselp.u32 %0, 1, 0, p;\n}"
      : "=r"(done) : "r"(bar), "r"(parity) : "memory");
  return done != 0;
}
__device__ __forceinline__ void tma2d(uint32_t dst, const CUtensorMap* m, int c0, int c1, uint32_t bar, uint64_t pol) {
  asm volatile(
      "cp.async.bulk.tensor.2d.shared::cluster.global.mbarrier::complete_tx::bytes.L2::cache_hint [%0], [%1, {%3, %4}], [%2], %5;"
      ::"r"(dst), "l"(m), "r"(bar), "r"(c0), "r"(c1), "l"(pol) : "memory");
}
__device__ __forceinline__ void tma3d(uint32_t dst, const CUtensorMap* m, int c0, int c1, int c2, uint32_t bar, uint64_t pol) {
  asm volatile(
      "cp.async.bulk.tensor.3d.shared::cluster.global.mbarrier::complete_tx::bytes.L2::cache_hint [%0], [%1, {%3, %4, %5}], [%2], %6;"
      ::"r"(dst), "l"(m), "r"(bar), "r"(c0), "r"(c1), "r"(c2), "l"(pol) : "memory");
}
__device__ __forceinline__ void tma4d(uint32_t dst, const CUtensorMap* m, int c0, int c1, int c2, int c3, uint32_t bar, uint64_t pol) {
  asm volatile(
      "cp.async.bulk.tensor.4d.shared::cluster.global.mbarrier::complete_tx::bytes.L2::cache_hint [%0], [%1, {%3, %4, %5, %6}], [%2], %7;"
      ::"r"(dst), "l"(m), "r"(bar), "r"(c0), "r"(c1), "r"(c2), "r"(c3), "l"(pol) : "memory");
}
__device__ __forceinline__ void cp_async16(uint32_t dst, const void* src) {
  asm volatile("cp.async.cg.shared.global.L2::128B [%0], [%1], 16;" ::"r"(dst), "l"(src) : "memory");
}
__device__ __forceinline__ void ldsm4(uint32_t (&r)[4], uint32_t addr) {
  asm volatile("ldmatrix.sync.aligned.m8n8.x4.shared.b16 {%0,%1,%2,%3}, [%4];"
               : "=r"(r[0]), "=r"(r[1]), "=r"(r[2]), "=r"(r[3]) : "r"(addr) : "memory");
}
__device__ __forceinline__ void ldsm4t(uint32_t (&r)[4], uint32_t addr) {
  asm volatile("ldmatrix.sync.aligned.m8n8.x4.trans.shared.b16 {%0,%1,%2,%3}, [%4];"
               : "=r"(r[0]), "=r"(r[1]), "=r"(r[2]), "=r"(r[3]) : "r"(addr) : "memory");
}
__device__ __forceinline__ void mma16816(float (&c)[4], const uint32_t (&a)[4], uint32_t b0, uint32_t b1) {
  asm(
      "mma.sync.aligned.m16n8k16.row.col.f32.bf16.bf16.f32 {%0,%1,%2,%3}, {%4,%5,%6,%7}, {%8,%9}, {%0,%1,%2,%3};"
      : "+f"(c[0]), "+f"(c[1]), "+f"(c[2]), "+f"(c[3])
      : "r"(a[0]), "r"(a[1]), "r"(a[2]), "r"(a[3]), "r"(b0), "r"(b1));
}
__device__ __forceinline__ uint32_t movmat(uint32_t a) {
  uint32_t d;
  asm volatile("movmatrix.sync.aligned.m8n8.trans.b16 %0, %1;" : "=r"(d) : "r"(a));
  return d;
}
__device__ __forceinline__ float ex2(float x) {
  float y;
  asm("ex2.approx.ftz.f32 %0, %1;" : "=f"(y) : "f"(x));
  return y;
}
__device__ __forceinline__ uint32_t pack_bf16(float lo, float hi) {
  uint32_t r;
  asm("cvt.rn.bf16x2.f32 %0, %1, %2;" : "=r"(r) : "f"(hi), "f"(lo));
  return r;
}
__device__ __forceinline__ float bf16r(float x) { return __bfloat162float(__float2bfloat16_rn(x)); }
__device__ __forceinline__ float silu_f(float x) { return x / (1.0f + __expf(-x)); }
__device__ __forceinline__ float warp_max(float x) {
  int i = __float_as_int(x);
  i ^= (i >> 31) & 0x7fffffff;
  i = __reduce_max_sync(0xffffffffu, i);
  i ^= (i >> 31) & 0x7fffffff;
  return __int_as_float(i);
}
__device__ __forceinline__ void bar_sync(int id, int n) { asm volatile("bar.sync %0, %1;" ::"r"(id), "r"(n) : "memory"); }
__device__ __forceinline__ void bar_arrive(int id, int n) { asm volatile("bar.arrive %0, %1;" ::"r"(id), "r"(n) : "memory"); }
__device__ __forceinline__ void red_release(unsigned* p, unsigned v) {
  asm volatile("red.release.gpu.global.add.u32 [%0], %1;" ::"l"(p), "r"(v) : "memory");
}
__device__ __forceinline__ void red_relaxed(unsigned* p, unsigned v) {
  asm volatile("red.relaxed.gpu.global.add.u32 [%0], %1;" ::"l"(p), "r"(v) : "memory");
}
__device__ __forceinline__ unsigned ld_acquire(const unsigned* p) {
  unsigned v;
  asm volatile("ld.acquire.gpu.global.u32 %0, [%1];" : "=r"(v) : "l"(p) : "memory");
  return v;
}
__device__ __forceinline__ unsigned atom_add(unsigned* p, unsigned v) {
  unsigned r;
  asm volatile("atom.relaxed.gpu.global.add.u32 %0, [%1], %2;" : "=r"(r) : "l"(p), "r"(v) : "memory");
  return r;
}
__device__ __forceinline__ void poll_ge(const unsigned* p, unsigned target, unsigned sleep_ns) {
  int it = 0;
  while (ld_acquire(p) < target) {
    if (sleep_ns) __nanosleep(sleep_ns);
    if (++it > kSpinLimit) __trap();
  }
}
__device__ __forceinline__ float4 ldx4(const float* p) {
  float4 v;
  asm volatile("ld.relaxed.gpu.global.v4.f32 {%0,%1,%2,%3}, [%4];" : "=f"(v.x), "=f"(v.y), "=f"(v.z), "=f"(v.w) : "l"(p) : "memory");
  return v;
}
__device__ __forceinline__ float nz(float v) { return __float_as_uint(v) == 0u ? -0.0f : v; }
__device__ __forceinline__ void stx4(float* p, float4 v) {
  asm volatile("st.relaxed.gpu.global.v4.f32 [%0], {%1,%2,%3,%4};" ::"l"(p), "f"(nz(v.x)), "f"(nz(v.y)), "f"(nz(v.z)), "f"(nz(v.w)) : "memory");
}
__device__ __forceinline__ void stx2(float* p, float a, float b) {
  asm volatile("st.relaxed.gpu.global.v2.f32 [%0], {%1,%2};" ::"l"(p), "f"(nz(a)), "f"(nz(b)) : "memory");
}
__device__ __forceinline__ void stx1(float* p, float a) {
  asm volatile("st.relaxed.gpu.global.f32 [%0], %1;" ::"l"(p), "f"(nz(a)) : "memory");
}
__device__ __forceinline__ void clr4(float* p) {
  asm volatile("st.relaxed.gpu.global.v4.f32 [%0], {%1,%1,%1,%1};" ::"l"(p), "f"(0.0f) : "memory");
}
__device__ __forceinline__ bool full4(const float4& v) {
  return __float_as_uint(v.x) != 0u && __float_as_uint(v.y) != 0u && __float_as_uint(v.z) != 0u && __float_as_uint(v.w) != 0u;
}
__device__ __forceinline__ void gather18(float4 (&v)[18], const float* po, const float* pml) {
#pragma unroll
  for (int k = 0; k < 18; k++) v[k] = ldx4(k < 16 ? po + k * 1024 : pml + (k - 16) * 128);
  for (int it = 0;; it++) {
    bool ok = true;
#pragma unroll
    for (int k = 0; k < 18; k++) ok = ok && full4(v[k]);
    if (__all_sync(0xffffffffu, ok)) break;
    if (it > kSpinLimit) __trap();
    __nanosleep(40);
#pragma unroll
    for (int k = 0; k < 18; k++)
      if (!full4(v[k])) v[k] = ldx4(k < 16 ? po + k * 1024 : pml + (k - 16) * 128);
  }
}

__device__ __forceinline__ void load_wo(uint32_t (&a)[18][4], uint32_t base, int w, int lane) {
  const uint32_t wl = ((lane & 7) + (lane >> 4) * 8) * 128 + ((((lane >> 3) & 1) ^ (lane & 7)) << 4);
#pragma unroll
  for (int mt = 0; mt < 9; mt++) {
    const int tile = w * 9 + mt;
    const uint32_t ad = base + (tile >> 2) * 4096 + (wl ^ ((tile & 3) << 5));
    ldsm4t(a[2 * mt], ad);
    ldsm4t(a[2 * mt + 1], ad + 2048);
  }
}

struct Maps {
  CUtensorMap wg, wu, wd, k, v, wo;
};

__global__ void __launch_bounds__(kThreads, 1)
fused_decode_kernel(const char* __restrict__ wqp, const __nv_bfloat16* __restrict__ x,
                    __nv_bfloat16* __restrict__ out, Scratch* sc, const __grid_constant__ Maps maps) {
  if (threadIdx.x == 224 && blockIdx.x < kSliceCtas)
    asm volatile("cp.async.bulk.prefetch.L2.global [%0], %1;" ::"l"(wqp + (size_t)blockIdx.x * 36864), "r"(36864) : "memory");
  extern __shared__ unsigned char smem_dyn[];
  unsigned char* sm = smem_dyn + ((1024u - (smem_u32(smem_dyn) & 1023u)) & 1023u);
  const uint32_t sb = smem_u32(sm);
  const int tid = threadIdx.x, warp = tid >> 5, lane = tid & 31;
  const int cta = blockIdx.x, G = gridDim.x;
  const uint32_t barFull = sb + kOffBar, barEmpty = barFull + kSlots * 8, barInfo = barEmpty + kSlots * 8;
  const uint32_t barMfull = barInfo + kSlots * 8, barMempty = barMfull + 16;
  const uint32_t barWo = barMempty + 16, barD = barWo + 8, barQ = barD + 8, barQok = barQ + 8;
  const uint32_t barFree = barQok + 8;
  volatile int* info = reinterpret_cast<volatile int*>(sm + kOffInfo);
  constexpr int kLastBatch = kNAtt - kHKV * kItemsPerPair;

  uint2 xr[9];
  if (warp < 4) {
    const uint2* xp = reinterpret_cast<const uint2*>(x + (warp * 2 + (lane >> 4)) * kD) + (lane & 15);
#pragma unroll
    for (int i = 0; i < 9; i++) xr[i] = __ldg(xp + i * 16);
    if (cta < kSliceCtas) {
      const uint32_t dst = sb + kOffW + warp * 9216 + (lane >> 2) * 64 + (((lane & 3) ^ ((lane >> 3) & 3)) << 4);
      const char* src = wqp + (size_t)(warp * 144 + (lane >> 2)) * 8192 + cta * 64 + (lane & 3) * 16;
#pragma unroll 1
      for (int i = 0; i < 18; i++) cp_async16(dst + i * 512, src + (size_t)i * 65536);
      asm volatile("cp.async.commit_group;" ::: "memory");
    }
  }
  if (warp == 5 && lane < 6)
    asm volatile("prefetch.tensormap [%0];" ::"l"(reinterpret_cast<const CUtensorMap*>(&maps) + lane) : "memory");
  unsigned nextDyn = 0;
  uint64_t pol = 0;
  if (tid == 128) {
    nextDyn = atom_add(&sc->ctr.claim, 1);
#pragma unroll
    for (int i = 0; i < kNumBars; i++) mbar_init(barFull + i * 8, ((kBarCount4 >> i) & 1) ? 4 : 1);
    asm volatile("fence.mbarrier_init.release.cluster;" ::: "memory");
    asm volatile("createpolicy.fractional.L2::evict_first.b64 %0, 1.0;" : "=l"(pol));
#pragma unroll 1
    for (int w = 0; w < kSlots; w++) {
      info[w] = cta;
      mbar_arrive(barInfo + w * 8);
      mbar_expect_tx(barFull + w * 8, 9216);
      tma2d(sb + kOffRing + w * kSlotBytes, &maps.wg + (w >> 2), cta * 32, (w & 3) * 144, barFull + w * 8, pol);
    }
  }
  __syncthreads();

  if (warp >= 4) {
  if (warp == 4) {
    if (lane == 0) {
      int item = cta, n = kSlots;
      while (true) {
        const int nsub = item < kNFfn ? 12 : 4;
#pragma unroll 1
        for (int w = item == cta ? kSlots : 0; w < nsub; w++, n++) {
          const int slot = n & (kSlots - 1);
          mbar_wait(barEmpty + slot * 8, ((n / kSlots) & 1) ^ 1);
          info[slot] = item;
          mbar_arrive(barInfo + slot * 8);
          const uint32_t fb = barFull + slot * 8;
          const uint32_t dst = sb + kOffRing + slot * kSlotBytes;
          if (item >= kNFfn) {
            if (item < kNItems) {
              mbar_expect_tx(fb, kSlotBytes);
              const int row = (item - kNFfn) * kItemRows + w * 32;
              tma3d(dst, &maps.k, 0, row, 0, fb, pol);
              tma3d(dst + 8192, &maps.v, 0, row, 0, fb, pol);
            }
          } else {
            mbar_expect_tx(fb, 9216);
            const int c = (w & 3) * 144;
            if (w < 8) tma2d(dst, w < 4 ? &maps.wg : &maps.wu, item * 32, c, fb, pol);
            else tma2d(dst, &maps.wd, c, item * 32, fb, pol);
          }
        }
        if (item >= kNItems) break;
        if (item + G < kNFfn) {
          item += G;
          continue;
        }
        item = (int)nextDyn + kNFfn;
        if (item < kNItems) nextDyn = atom_add(&sc->ctr.claim, 1);
      }
      if (cta < kSliceCtas) {
        mbar_wait(barFull + ((n - 5) & (kSlots - 1)) * 8, ((n - 5) / kSlots) & 1);
        mbar_expect_tx(barWo, 36864);
        tma4d(sb + kOffW, &maps.wo, 0, (cta & 7) * 16, (cta >> 3) * 2, 0, barWo, pol);
      }
    }
  } else if (warp == 5) {
    const float* mb = reinterpret_cast<const float*>(sm + kOffMbuf);
    int pend = -1;
    int batch = 0;
    if (lane == 0) {
      if (cta < kSliceCtas) {
        mbar_wait(barQ, 0);
        red_release(&sc->ctr.qready, 1);
      }
      poll_ge(&sc->ctr.qready, kSliceCtas, 50);
      mbar_arrive(barQok);
    }
    __syncwarp();
    for (int kk = 0;; kk++) {
      const int buf = kk & 1;
      mbar_wait(barMfull + buf * 8, (kk >> 1) & 1);
      const float* p = mb + buf * 4 * kMbufStride;
      const int item = __float_as_int(p[260]);
      if (pend >= 0 && lane == 0) red_release(&sc->ctr.done[pend * 32], 1);
      if (item < 0) break;
      if ((item >> 10) != batch) {
        batch = item >> 10;
        if (batch >= 2) mbar_wait(barFree + (batch - 2) * 8, 0);
      }
      float4 ml[4];
#pragma unroll
      for (int w = 0; w < 4; w++) ml[w] = *reinterpret_cast<const float4*>(p + w * kMbufStride + 256);
      const float M0 = fmaxf(fmaxf(ml[0].x, ml[1].x), fmaxf(ml[2].x, ml[3].x));
      const float M1 = fmaxf(fmaxf(ml[0].z, ml[1].z), fmaxf(ml[2].z, ml[3].z));
      float4 a = make_float4(0.f, 0.f, 0.f, 0.f), b = a;
      float L0 = 0.f, L1 = 0.f;
#pragma unroll
      for (int w = 0; w < 4; w++) {
        const float s0 = ex2(ml[w].x - M0), s1 = ex2(ml[w].z - M1);
        L0 = fmaf(s0, ml[w].y, L0);
        L1 = fmaf(s1, ml[w].w, L1);
        const float4 u = *reinterpret_cast<const float4*>(p + w * kMbufStride + lane * 4);
        const float4 v = *reinterpret_cast<const float4*>(p + w * kMbufStride + 128 + lane * 4);
        a.x = fmaf(s0, u.x, a.x); a.y = fmaf(s1, u.y, a.y); a.z = fmaf(s0, u.z, a.z); a.w = fmaf(s1, u.w, a.w);
        b.x = fmaf(s0, v.x, b.x); b.y = fmaf(s1, v.y, b.y); b.z = fmaf(s0, v.z, b.z); b.w = fmaf(s1, v.w, b.w);
      }
      float* dst = sc->po + (size_t)PSLOT(item >> 6) * (kItemsPerPair * 256) + (item & 63) * 256;
      stx4(dst + lane * 4, a);
      stx4(dst + 128 + lane * 4, b);
      if (lane < 8)
        stx4(reinterpret_cast<float*>(sc->pml + (PSLOT(item >> 6) * 8 + lane) * kItemsPerPair + (item & 63)), make_float4(M0, L0, M1, L1));
      __syncwarp();
      pend = item >> 6;
      if (lane == 0) mbar_arrive(barMempty + buf * 8);
      if (item >= kLastBatch - 5 * kItemsPerPair) {
        if (item < kLastBatch && lane == 0) red_release(&sc->ctr.done[pend * 32], 1);
        pend = -1;
      }
    }
  } else {
    const int cw = warp - 6;
    const int ci64 = tid - 192;
    mbar_wait(barQok, 0);
    if (ci64 == 0) {
      mbar_wait(barD, 0);
      red_release(&sc->ctr.ddone, 1);
    }
    if (cta < kSliceCtas) {
      if (lane == 0) poll_ge(&sc->ctr.ddone, G, 500);
      __syncwarp();
      float* ssum = reinterpret_cast<float*>(sm + kOffSsum);
      if (ci64 < 63) {
        const int q = ci64 % 9, pg = ci64 / 9;
        float4 acc = make_float4(0.f, 0.f, 0.f, 0.f);
#pragma unroll 4
        for (int p = pg; p < G; p += 7) {
          const float4 v = ldx4(sc->dp + p * kOutElems + cta * 36 + q * 4);
          acc.x += v.x; acc.y += v.y; acc.z += v.z; acc.w += v.w;
        }
        *reinterpret_cast<float4*>(ssum + pg * 36 + q * 4) = acc;
      }
      float* g7 = reinterpret_cast<float*>(sm + kOffG7);
      if (cta < kRow7Ctas) {
        float acc = 0.f;
#pragma unroll 4
        for (int p = ci64 >> 3; p < G; p += 8) acc += __ldcg(sc->dp + p * kOutElems + (cta * 8 + (ci64 & 7)) * 8 + 7);
        g7[ci64] = acc;
      }
      bar_sync(2, 64);
      if (cta < kRow7Ctas && ci64 >= 56) {
        float d = 0.f;
#pragma unroll
        for (int k = 0; k < 8; k++) d += g7[k * 8 + (ci64 & 7)];
        g7[64 + (ci64 & 7)] = bf16r(silu_f(bf16r(d)));
      }
      if (ci64 < 36) {
        float d = 0.f;
#pragma unroll
        for (int k = 0; k < 7; k++) d += ssum[k * 36 + ci64];
        ssum[252 + ci64] = bf16r(silu_f(bf16r(d)));
      }
      const int kvh = cta >> 3, sl = cta & 7;
      float2* wbuf = reinterpret_cast<float2*>(sm + kOffWbuf) + cw * 64;
      __nv_bfloat16* os = reinterpret_cast<__nv_bfloat16*>(sm + kOffOs);
      const int ci = lane >> 3, q4 = lane & 7;
#pragma unroll 1
      for (int b = cw; b < kB; b += 2) {
        const int pair = b * kHKV + kvh;
        if (b == 4 + cw) {
#pragma unroll 2
          for (int k = 0; k < 18; k++) clr4(sc->sp + cta * kOutElems + (k * 64 + ci64) * 4);
          const int pair7 = PSLOT(7 * kHKV + kvh);
#pragma unroll 2
          for (int k = 0; k < 8; k++)
            clr4(sc->po + ((size_t)pair7 * kItemsPerPair + k * 8 + (ci64 >> 3)) * 256 + sl * 32 + (ci64 & 7) * 4);
          clr4(reinterpret_cast<float*>(sc->pml + (pair7 * 8 + sl) * kItemsPerPair + ci64));
          if (cta < kRow7Ctas) {
#pragma unroll
            for (int k = 0; k < 4; k++) clr4(sc->s7 + cta * 1024 + (k * 64 + ci64) * 4);
          }
          __syncwarp();
          if (lane == 0) red_release(&sc->ctr.zready, 1);
        }
        if (b >= 2 && lane == 0) {
          if (b == 7) poll_ge(&sc->ctr.zready, kSliceCtas * 2, 200);
          else poll_ge(&sc->ctr.cons[(b - 2) * 32], kSliceCtas, 200);
          mbar_arrive(barFree + (b - 2) * 8);
        }
        if (b == 7) break;
        const float* pml = reinterpret_cast<const float*>(sc->pml + (PSLOT(pair) * 8 + sl) * kItemsPerPair);
        if (lane == 0) poll_ge(&sc->ctr.done[pair * 32], kItemsPerPair, b == 6 ? 100 : 300);
        __syncwarp();
        const float* po = sc->po + (size_t)PSLOT(pair) * kItemsPerPair * 256 + sl * 32 + q4 * 4 + ci * 256;
        float4 v[18];
        gather18(v, po, pml + lane * 4);
        __syncwarp();
        if (lane == 0 && b < 5) red_release(&sc->ctr.cons[b * 32], 1);
        const float4 mlA = v[16], mlB = v[17];
        const float M0 = warp_max(fmaxf(mlA.x, mlB.x)), M1 = warp_max(fmaxf(mlA.z, mlB.z));
        const float wA0 = ex2(mlA.x - M0), wA1 = ex2(mlA.z - M1), wB0 = ex2(mlB.x - M0), wB1 = ex2(mlB.z - M1);
        float L0 = wA0 * mlA.y + wB0 * mlB.y, L1 = wA1 * mlA.w + wB1 * mlB.w;
        wbuf[lane] = make_float2(wA0, wA1);
        wbuf[32 + lane] = make_float2(wB0, wB1);
        __syncwarp();
        float4 acc = make_float4(0.f, 0.f, 0.f, 0.f);
#pragma unroll
        for (int k = 0; k < 16; k++) {
          const float2 w2 = wbuf[k * 4 + ci];
          acc.x = fmaf(w2.x, v[k].x, acc.x); acc.y = fmaf(w2.y, v[k].y, acc.y);
          acc.z = fmaf(w2.x, v[k].z, acc.z); acc.w = fmaf(w2.y, v[k].w, acc.w);
        }
#pragma unroll
        for (int o = 1; o <= 16; o <<= 1) {
          L0 += __shfl_xor_sync(0xffffffffu, L0, o);
          L1 += __shfl_xor_sync(0xffffffffu, L1, o);
          if (o >= 8) {
            acc.x += __shfl_xor_sync(0xffffffffu, acc.x, o); acc.y += __shfl_xor_sync(0xffffffffu, acc.y, o);
            acc.z += __shfl_xor_sync(0xffffffffu, acc.z, o); acc.w += __shfl_xor_sync(0xffffffffu, acc.w, o);
          }
        }
        if (lane < 8) {
          const float r0 = 1.0f / L0, r1 = 1.0f / L1;
          *reinterpret_cast<uint32_t*>(os + b * 40 + q4 * 2) = pack_bf16(acc.x * r0, acc.z * r0);
          *reinterpret_cast<uint32_t*>(os + b * 40 + 16 + q4 * 2) = pack_bf16(acc.y * r1, acc.w * r1);
        }
        __syncwarp();
      }
      __syncwarp();
      if (cta < kRow7Ctas) bar_arrive(4, 192);
    } else if (lane == 0) {
      for (int b = 2 + cw; b < kB; b += 2) {
        if (b == 7) poll_ge(&sc->ctr.zready, kSliceCtas * 2, 500);
        else poll_ge(&sc->ctr.cons[(b - 2) * 32], kSliceCtas, 500);
        mbar_arrive(barFree + (b - 2) * 8);
      }
    }
  }
    __syncwarp();
    if (cta < kSliceCtas) {
      const int aw = warp - 4, at = tid - 128;
      const int g = lane >> 2, t = lane & 3;
      const int oe = cta * 36 + at;
      float xv = 0.f;
      if (at < 36) xv = __bfloat162float(x[(oe & 7) * kD + (oe >> 3)]);
      mbar_wait(barFree + 5 * 8, 0);
      mbar_wait(barWo, 0);
      uint32_t a[18][4];
      load_wo(a, sb + kOffW, aw, lane);
      bar_sync(3, 128);
      uint32_t ob[4] = {0u, 0u, 0u, 0u};
      if (g < 7) {
        const __nv_bfloat16* os = reinterpret_cast<const __nv_bfloat16*>(sm + kOffOs) + g * 40 + t * 2;
#pragma unroll
        for (int j = 0; j < 4; j++) ob[j] = *reinterpret_cast<const uint32_t*>(os + j * 8);
      }
#pragma unroll
      for (int mt = 0; mt < 9; mt++) {
        float c[4] = {0.f, 0.f, 0.f, 0.f};
        mma16816(c, a[2 * mt], ob[0], ob[1]);
        mma16816(c, a[2 * mt + 1], ob[2], ob[3]);
#pragma unroll
        for (int h = 0; h < 2; h++) {
          const int e = ((mt * 2 + h) * 8 + g) * 8 + t * 2, u = e / 36;
          stx2(sc->sp + ((aw * 32 + u) * kSliceCtas + cta) * 36 + (e - u * 36), c[2 * h], c[2 * h + 1]);
        }
      }
      bar_sync(5, 256);
      const float* fp = sc->sp + cta * kOutElems + at * 4;
      const int fcnt = at < 18 ? 10 : (at < 126 ? 9 : 0);
      float4 f[10];
#pragma unroll
      for (int k = 0; k < 10; k++) f[k] = k < fcnt ? ldx4(fp + k * 504) : make_float4(-0.f, -0.f, -0.f, -0.f);
      for (int it = 0;; it++) {
        bool ok = true;
#pragma unroll
        for (int k = 0; k < 10; k++) ok = ok && full4(f[k]);
        if (__all_sync(0xffffffffu, ok)) break;
        if (it > kSpinLimit) __trap();
        __nanosleep(40);
#pragma unroll
        for (int k = 0; k < 10; k++)
          if (!full4(f[k])) f[k] = ldx4(fp + k * 504);
      }
      float* fsum = reinterpret_cast<float*>(sm + kOffFsum);
      float4 acc = f[0];
#pragma unroll
      for (int k = 1; k < 10; k++) { acc.x += f[k].x; acc.y += f[k].y; acc.z += f[k].z; acc.w += f[k].w; }
      if (at < 126) *reinterpret_cast<float4*>(fsum + at * 4) = acc;
      bar_sync(3, 128);
      if (at < 36 && (oe & 7) != 7) {
        float s = 0.f;
#pragma unroll
        for (int k = 0; k < 14; k++) s += fsum[k * 36 + at];
        const float gt = reinterpret_cast<const float*>(sm + kOffSsum)[252 + at];
        out[(oe & 7) * kD + (oe >> 3)] = __float2bfloat16_rn(xv + bf16r(bf16r(s) * gt));
      }
    }
  } else {
    const int g = lane >> 2, t = lane & 3;
    __nv_bfloat16* xn = reinterpret_cast<__nv_bfloat16*>(sm + kOffXn);
    {
      float v[36];
#pragma unroll
      for (int i = 0; i < 9; i++) {
        v[4 * i] = __uint_as_float(xr[i].x << 16);
        v[4 * i + 1] = __uint_as_float(xr[i].x & 0xffff0000u);
        v[4 * i + 2] = __uint_as_float(xr[i].y << 16);
        v[4 * i + 3] = __uint_as_float(xr[i].y & 0xffff0000u);
      }
      float s = 0.f;
#pragma unroll
      for (int i = 0; i < 36; i++) s += v[i];
#pragma unroll
      for (int o = 8; o > 0; o >>= 1) s += __shfl_xor_sync(0xffffffffu, s, o);
      const float mean = s * (1.0f / kD);
      float q = 0.f;
#pragma unroll
      for (int i = 0; i < 36; i++) { const float d = v[i] - mean; q = fmaf(d, d, q); }
#pragma unroll
      for (int o = 8; o > 0; o >>= 1) q += __shfl_xor_sync(0xffffffffu, q, o);
      const float mb = bf16r(mean);
      const float rden = 1.0f / bf16r(sqrtf(bf16r(bf16r(q * (1.0f / kD)) + 1e-5f)));
      __nv_bfloat16* xw = xn + (warp * 2 + (lane >> 4)) * kXnPitch + (lane & 15) * 4;
#pragma unroll
      for (int i = 0; i < 9; i++)
        *reinterpret_cast<uint2*>(xw + i * 64) =
            make_uint2(pack_bf16(bf16r(v[4 * i] - mb) * rden, bf16r(v[4 * i + 1] - mb) * rden),
                       pack_bf16(bf16r(v[4 * i + 2] - mb) * rden, bf16r(v[4 * i + 3] - mb) * rden));
    }
    bar_sync(1, 128);
    float* mb = reinterpret_cast<float*>(sm + kOffMbuf);
    const uint32_t r8 = lane & 7;
    const uint32_t guLane = (r8 + (lane >> 4) * 8) * 64 + ((((lane >> 3) & 1) ^ (r8 >> 1)) << 4);
    int slot = warp, item;
    uint32_t fph = 0;
    {
      uint32_t xb[9][2];
#pragma unroll
      for (int ks = 0; ks < 9; ks++) {
        xb[ks][0] = *reinterpret_cast<const uint32_t*>(xn + g * kXnPitch + warp * 144 + ks * 16 + t * 2);
        xb[ks][1] = *reinterpret_cast<const uint32_t*>(xn + g * kXnPitch + warp * 144 + ks * 16 + 8 + t * 2);
      }
      if (cta < kSliceCtas) {
        if (tid == 0) {
          sc->ctr.done[cta * 32] = 0;
          if (cta < 8) sc->ctr.cons[cta * 32] = 0;
          if (cta == 0) { sc->ctr.ddone = 0; sc->ctr.zready = 0; sc->ctr.exitc = 0; }
        }
        asm volatile("cp.async.wait_group 0;" ::: "memory");
        __syncwarp();
        const uint32_t lo = sb + kOffW + warp * 9216;
        uint32_t a[18][4];
#pragma unroll
        for (int i = 0; i < 18; i++) ldsm4t(a[i], lo + (guLane ^ ((i & 1) * 32)) + (i >> 1) * 1024);
        float c[2][4] = {{0.f, 0.f, 0.f, 0.f}, {0.f, 0.f, 0.f, 0.f}};
#pragma unroll
        for (int i = 0; i < 18; i++) mma16816(c[i & 1], a[i], xb[i >> 1][0], xb[i >> 1][1]);
        float* qr = mb + warp * 256;
#pragma unroll
        for (int mt = 0; mt < 2; mt++) {
          *reinterpret_cast<float2*>(qr + (mt * 16 + g) * 8 + t * 2) = make_float2(c[mt][0], c[mt][1]);
          *reinterpret_cast<float2*>(qr + (mt * 16 + 8 + g) * 8 + t * 2) = make_float2(c[mt][2], c[mt][3]);
        }
        bar_sync(1, 128);
        const int b = tid >> 4, cp = tid & 15;
        float q0 = 0.f, q1 = 0.f;
#pragma unroll
        for (int w = 0; w < 4; w++) {
          q0 += mb[w * 256 + (cp * 2) * 8 + b];
          q1 += mb[w * 256 + (cp * 2 + 1) * 8 + b];
        }
        const int col = cta * 32 + cp * 2;
        const int head = col >> 7, d = col & 127;
        const int pos = (head & 1) * 128 + (d >> 5) * 32 + ((d & 7) >> 1) * 8 + ((d >> 4) & 1) * 4 + ((d >> 3) & 1) * 2;
        *reinterpret_cast<uint32_t*>(sc->q + (b * kHKV + (head >> 1)) * 256 + pos) = pack_bf16(q0, q1);
        __syncwarp();
        if (lane == 0) mbar_arrive(barQ);
      } else {
        bar_sync(1, 128);
      }

      float dacc[9][4];
#pragma unroll
      for (int i = 0; i < 9; i++) dacc[i][0] = dacc[i][1] = dacc[i][2] = dacc[i][3] = 0.f;
      float* red = reinterpret_cast<float*>(sm + kOffXn);
      const uint32_t dnLane = (r8 + (lane >> 4) * 8) * 288 + ((lane >> 3) & 1) * 16;
      while (true) {
        mbar_wait(barInfo + slot * 8, fph);
        item = info[slot];
        if (item >= kNFfn) break;
        uint32_t a[18][4];
        float* rw = red + warp * 512;
#pragma unroll 1
        for (int gu = 0; gu < 2; gu++) {
          mbar_wait(barFull + slot * 8, fph);
          const uint32_t base = sb + kOffRing + slot * kSlotBytes;
#pragma unroll
          for (int i = 0; i < 18; i++) ldsm4t(a[i], base + (guLane ^ ((i & 1) * 32)) + (i >> 1) * 1024);
          float c[2][4] = {{0.f, 0.f, 0.f, 0.f}, {0.f, 0.f, 0.f, 0.f}};
#pragma unroll
          for (int i = 0; i < 18; i++) mma16816(c[i & 1], a[i], xb[i >> 1][0], xb[i >> 1][1]);
#pragma unroll
          for (int mt = 0; mt < 2; mt++) {
            float* r = rw + gu * 256 + (2 * t) * 32 + mt * 16 + g;
            r[0] = c[mt][0]; r[32] = c[mt][1]; r[8] = c[mt][2]; r[40] = c[mt][3];
          }
          __syncwarp();
          if (lane == 0) mbar_arrive(barEmpty + slot * 8);
          slot += 4;
          if (slot >= kSlots) { slot -= kSlots; fph ^= 1; }
        }
        bar_sync(1, 128);
        uint32_t hb[4];
#pragma unroll
        for (int j = 0; j < 4; j++) {
          float2 gs = make_float2(0.f, 0.f), us = gs;
#pragma unroll
          for (int w = 0; w < 4; w++) {
            const float* rr = red + w * 512 + g * 32 + j * 8 + t * 2;
            const float2 a2 = *reinterpret_cast<const float2*>(rr), b2 = *reinterpret_cast<const float2*>(rr + 256);
            gs.x += a2.x; gs.y += a2.y; us.x += b2.x; us.y += b2.y;
          }
          hb[j] = pack_bf16(bf16r(silu_f(bf16r(gs.x))) * bf16r(us.x), bf16r(silu_f(bf16r(gs.y))) * bf16r(us.y));
        }
        mbar_wait(barFull + slot * 8, fph);
        const uint32_t base = sb + kOffRing + slot * kSlotBytes + dnLane;
#pragma unroll
        for (int i = 0; i < 18; i++) ldsm4t(a[i], base + (i >> 1) * 32 + (i & 1) * 4608);
#pragma unroll
        for (int i = 0; i < 18; i++) mma16816(dacc[i >> 1], a[i], hb[(i & 1) * 2], hb[(i & 1) * 2 + 1]);
        bar_sync(1, 128);
        if (lane == 0) mbar_arrive(barEmpty + slot * 8);
        slot += 4;
        if (slot >= kSlots) { slot -= kSlots; fph ^= 1; }
      }
      float* dp = sc->dp + cta * kOutElems + (warp * 144 + g) * 8 + t * 2;
#pragma unroll
      for (int mt = 0; mt < 9; mt++) {
        *reinterpret_cast<float2*>(dp + mt * 128) = make_float2(dacc[mt][0], dacc[mt][1]);
        *reinterpret_cast<float2*>(dp + mt * 128 + 64) = make_float2(dacc[mt][2], dacc[mt][3]);
      }
      __syncwarp();
      if (lane == 0) mbar_arrive(barD);
      mbar_wait(barQok, 0);
    }

    const float kScale = 0.08838834764831845f * 1.4426950408889634f;
    const uint32_t kLane = (r8 + ((lane >> 3) & 1) * 8) * 128 + (((lane >> 4) ^ r8) << 4);
    const uint32_t vLane = 8192 + (r8 + (lane >> 4) * 8) * 128 + ((((lane >> 3) & 1) ^ r8) << 4);
    int kk = 0;
    while (item < kNItems) {
      item -= kNFfn;
      uint4 qv[4];
      if (g < 2) {
        const uint4* qs = reinterpret_cast<const uint4*>(sc->q + (item >> 6) * 256 + g * 128 + t * 8);
#pragma unroll
        for (int i = 0; i < 4; i++) qv[i] = qs[i * 4];
      } else {
#pragma unroll
        for (int i = 0; i < 4; i++) qv[i] = make_uint4(0u, 0u, 0u, 0u);
      }
      mbar_wait(barFull + slot * 8, fph);
      const uint32_t base = sb + kOffRing + slot * kSlotBytes;
      uint32_t ka[16][4], va[16][4];
#pragma unroll
      for (int i = 0; i < 16; i++)
        ldsm4(ka[i], base + ((kLane ^ (((i >> 1) & 3) << 5)) + (i >> 3) * 4096 + (i & 1) * 2048));
#pragma unroll
      for (int i = 0; i < 16; i++)
        ldsm4t(va[i], base + ((vLane ^ (((i >> 1) & 3) << 5)) + (i >> 3) * 4096 + (i & 1) * 2048));
      float s[2][4], s2[2][4];
#pragma unroll
      for (int i = 0; i < 4; i++) s[0][i] = s[1][i] = s2[0][i] = s2[1][i] = 0.f;
#pragma unroll
      for (int kp = 0; kp < 4; kp++) {
        mma16816(s[0], ka[4 * kp], qv[kp].x, qv[kp].y);
        mma16816(s[1], ka[4 * kp + 1], qv[kp].x, qv[kp].y);
        mma16816(s2[0], ka[4 * kp + 2], qv[kp].z, qv[kp].w);
        mma16816(s2[1], ka[4 * kp + 3], qv[kp].z, qv[kp].w);
      }
#pragma unroll
      for (int i = 0; i < 4; i++) { s[0][i] += s2[0][i]; s[1][i] += s2[1][i]; }
      float m0 = fmaxf(fmaxf(s[0][0], s[0][2]), fmaxf(s[1][0], s[1][2]));
      float m1 = fmaxf(fmaxf(s[0][1], s[0][3]), fmaxf(s[1][1], s[1][3]));
#pragma unroll
      for (int o = 4; o <= 16; o <<= 1) {
        m0 = fmaxf(m0, __shfl_xor_sync(0xffffffffu, m0, o));
        m1 = fmaxf(m1, __shfl_xor_sync(0xffffffffu, m1, o));
      }
      m0 *= kScale; m1 *= kScale;
      float l0 = 0.f, l1 = 0.f;
      uint32_t pb[2][2];
#pragma unroll
      for (int mt = 0; mt < 2; mt++) {
        const float p0 = ex2(fmaf(s[mt][0], kScale, -m0)), p1 = ex2(fmaf(s[mt][1], kScale, -m1));
        const float p2 = ex2(fmaf(s[mt][2], kScale, -m0)), p3 = ex2(fmaf(s[mt][3], kScale, -m1));
        l0 += p0 + p2; l1 += p1 + p3;
        pb[mt][0] = movmat(pack_bf16(p0, p1));
        pb[mt][1] = movmat(pack_bf16(p2, p3));
      }
      float o_[8][4];
#pragma unroll
      for (int j = 0; j < 8; j++) {
        o_[j][0] = o_[j][1] = o_[j][2] = o_[j][3] = 0.f;
        mma16816(o_[j], va[2 * j], pb[0][0], pb[0][1]);
      }
#pragma unroll
      for (int j = 0; j < 8; j++) mma16816(o_[j], va[2 * j + 1], pb[1][0], pb[1][1]);
#pragma unroll
      for (int o = 4; o <= 16; o <<= 1) {
        l0 += __shfl_xor_sync(0xffffffffu, l0, o);
        l1 += __shfl_xor_sync(0xffffffffu, l1, o);
      }
      const int buf = kk & 1;
      mbar_wait(barMempty + buf * 8, ((kk >> 1) & 1) ^ 1);
      float* p = mb + (buf * 4 + warp) * kMbufStride;
      if (t == 0) {
#pragma unroll
        for (int j = 0; j < 8; j++) {
          *reinterpret_cast<float2*>(p + (j * 16 + g) * 2) = make_float2(o_[j][0], o_[j][1]);
          *reinterpret_cast<float2*>(p + (j * 16 + 8 + g) * 2) = make_float2(o_[j][2], o_[j][3]);
        }
        if (g == 0) {
          *reinterpret_cast<float4*>(p + 256) = make_float4(m0, l0, m1, l1);
          p[260] = __int_as_float(item);
        }
      }
      __syncwarp();
      if (lane == 0) {
        mbar_arrive(barMfull + buf * 8);
        mbar_arrive(barEmpty + slot * 8);
      }
      kk++;
      slot += 4;
      if (slot >= kSlots) { slot -= kSlots; fph ^= 1; }
      mbar_wait(barInfo + slot * 8, fph);
      item = info[slot];
    }
    {
      const int buf = kk & 1;
      mbar_wait(barMempty + buf * 8, ((kk >> 1) & 1) ^ 1);
      if (lane == 0) {
        mb[(buf * 4 + warp) * kMbufStride + 260] = __int_as_float(-1);
        mbar_arrive(barMfull + buf * 8);
        if (warp == 0) red_relaxed(&sc->ctr.exitc, 1);
      }
      __syncwarp();
    }
    if (cta < kSliceCtas) {
      float xv = 0.f;
      if (tid < 8 && cta < kRow7Ctas) xv = __bfloat162float(x[7 * kD + cta * 8 + tid]);
      mbar_wait(barFree + 5 * 8, 0);
      const int ps = PSLOT(7 * kHKV + (cta >> 3)), sl = cta & 7;
      const int ci = lane >> 3, q4 = lane & 7;
      const float* po = sc->po + (ps * kItemsPerPair + warp * 16 + ci) * 256 + sl * 32 + q4 * 4;
      const float* pml = reinterpret_cast<const float*>(sc->pml + (ps * 8 + sl) * kItemsPerPair + warp * 16 + (lane & 15));
      float4 v[5];
#pragma unroll
      for (int k = 0; k < 5; k++) v[k] = ldx4(k < 4 ? po + k * 1024 : pml);
      uint32_t a[18][4], ob[4];
      bool haveWo = false;
      for (int it = 0;; it++) {
        if (!haveWo && __all_sync(0xffffffffu, mbar_test(barWo, 0))) {
          load_wo(a, sb + kOffW, warp, lane);
          haveWo = true;
        }
        bool ok = true;
#pragma unroll
        for (int k = 0; k < 5; k++) ok = ok && full4(v[k]);
        if (__all_sync(0xffffffffu, ok) && haveWo) break;
        if (it > kSpinLimit) __trap();
#pragma unroll
        for (int k = 0; k < 5; k++)
          if (!full4(v[k])) v[k] = ldx4(k < 4 ? po + k * 1024 : pml);
      }
      float* cb = reinterpret_cast<float*>(sm + kOffCbuf);
      {
        const float M0 = warp_max(v[4].x), M1 = warp_max(v[4].z);
        const float w0 = ex2(v[4].x - M0), w1 = ex2(v[4].z - M1);
        float L0 = w0 * v[4].y, L1 = w1 * v[4].w;
        float4 acc = make_float4(0.f, 0.f, 0.f, 0.f);
#pragma unroll
        for (int k = 0; k < 4; k++) {
          const float a0 = __shfl_sync(0xffffffffu, w0, k * 4 + ci), a1 = __shfl_sync(0xffffffffu, w1, k * 4 + ci);
          acc.x = fmaf(a0, v[k].x, acc.x); acc.y = fmaf(a1, v[k].y, acc.y);
          acc.z = fmaf(a0, v[k].z, acc.z); acc.w = fmaf(a1, v[k].w, acc.w);
        }
#pragma unroll
        for (int o = 1; o <= 16; o <<= 1) {
          if (o <= 8) {
            L0 += __shfl_xor_sync(0xffffffffu, L0, o);
            L1 += __shfl_xor_sync(0xffffffffu, L1, o);
          }
          if (o >= 8) {
            acc.x += __shfl_xor_sync(0xffffffffu, acc.x, o); acc.y += __shfl_xor_sync(0xffffffffu, acc.y, o);
            acc.z += __shfl_xor_sync(0xffffffffu, acc.z, o); acc.w += __shfl_xor_sync(0xffffffffu, acc.w, o);
          }
        }
        if (lane < 8) {
          *reinterpret_cast<float2*>(cb + warp * 40 + q4 * 2) = make_float2(acc.x, acc.z);
          *reinterpret_cast<float2*>(cb + warp * 40 + 16 + q4 * 2) = make_float2(acc.y, acc.w);
          if (lane == 0) *reinterpret_cast<float4*>(cb + warp * 40 + 32) = make_float4(M0, L0, M1, L1);
        }
      }
      bar_sync(1, 128);
      {
        float4 ml[4];
#pragma unroll
        for (int w = 0; w < 4; w++) ml[w] = *reinterpret_cast<const float4*>(cb + w * 40 + 32);
        const float M0 = fmaxf(fmaxf(ml[0].x, ml[1].x), fmaxf(ml[2].x, ml[3].x));
        const float M1 = fmaxf(fmaxf(ml[0].z, ml[1].z), fmaxf(ml[2].z, ml[3].z));
        float L0 = 0.f, L1 = 0.f;
        float2 o2[4] = {{0.f, 0.f}, {0.f, 0.f}, {0.f, 0.f}, {0.f, 0.f}};
#pragma unroll
        for (int w = 0; w < 4; w++) {
          const float s0 = ex2(ml[w].x - M0), s1 = ex2(ml[w].z - M1);
          L0 = fmaf(s0, ml[w].y, L0);
          L1 = fmaf(s1, ml[w].w, L1);
#pragma unroll
          for (int j = 0; j < 4; j++) {
            const float2 u = *reinterpret_cast<const float2*>(cb + w * 40 + j * 8 + t * 2);
            o2[j].x = fmaf(j < 2 ? s0 : s1, u.x, o2[j].x);
            o2[j].y = fmaf(j < 2 ? s0 : s1, u.y, o2[j].y);
          }
        }
        const float r0 = __frcp_rn(L0), r1 = __frcp_rn(L1);
#pragma unroll
        for (int j = 0; j < 4; j++) ob[j] = pack_bf16(o2[j].x * (j < 2 ? r0 : r1), o2[j].y * (j < 2 ? r0 : r1));
      }
      {
        float c[10][4];
#pragma unroll
        for (int mt = 0; mt < 9; mt++) {
          c[mt][0] = c[mt][1] = c[mt][2] = c[mt][3] = 0.f;
          mma16816(c[mt], a[2 * mt], ob[0], ob[1]);
          mma16816(c[mt], a[2 * mt + 1], ob[2], ob[3]);
        }
        c[9][0] = c[9][2] = 0.f;
        float* s7 = sc->s7 + ((warp * 18 + t) * kSliceCtas + cta) * 8 + g;
#pragma unroll
        for (int k = 0; k < 5; k++) {
          const float lo = (t & 1) ? c[2 * k][2] : c[2 * k][0], hi = (t & 1) ? c[2 * k + 1][2] : c[2 * k + 1][0];
          if (k < 4 || t < 2) stx1(s7 + k * 4 * kSliceCtas * 8, (t & 2) ? hi : lo);
        }
      }
      bar_arrive(5, 256);
      if (cta < kRow7Ctas) {
        const float* hp = sc->s7 + cta * 1024 + tid * 4;
        float4 f0 = ldx4(hp), f1 = ldx4(hp + 512);
        for (int it = 0; !__all_sync(0xffffffffu, full4(f0) && full4(f1)); it++) {
          if (it > kSpinLimit) __trap();
          if (!full4(f0)) f0 = ldx4(hp);
          if (!full4(f1)) f1 = ldx4(hp + 512);
        }
        float* g7 = reinterpret_cast<float*>(sm + kOffG7);
        float4 h = make_float4(f0.x + f1.x, f0.y + f1.y, f0.z + f1.z, f0.w + f1.w);
#pragma unroll
        for (int o = 2; o <= 16; o <<= 1) {
          h.x += __shfl_xor_sync(0xffffffffu, h.x, o); h.y += __shfl_xor_sync(0xffffffffu, h.y, o);
          h.z += __shfl_xor_sync(0xffffffffu, h.z, o); h.w += __shfl_xor_sync(0xffffffffu, h.w, o);
        }
        if (lane < 2) *reinterpret_cast<float4*>(g7 + 72 + warp * 8 + lane * 4) = h;
        bar_sync(4, 192);
        if (tid < 8) {
          const float s = (g7[72 + tid] + g7[80 + tid]) + (g7[88 + tid] + g7[96 + tid]);
          out[7 * kD + cta * 8 + tid] = __float2bfloat16_rn(xv + bf16r(bf16r(s) * g7[64 + tid]));
        }
      }
      if (cta == 0 && tid == 96) {
        poll_ge(&sc->ctr.exitc, G, 20);
        sc->ctr.claim = 0;
        sc->ctr.qready = 0;
      }
    }
  }
}

__global__ void fb_ln(const __nv_bfloat16* x, float* xn) {
  const int lane = threadIdx.x;
  const __nv_bfloat16* xr = x + blockIdx.x * kD;
  float s = 0.f, q = 0.f;
  for (int i = lane; i < kD; i += 32) s += __bfloat162float(xr[i]);
  for (int o = 16; o > 0; o >>= 1) s += __shfl_xor_sync(0xffffffffu, s, o);
  const float mean = s * (1.0f / kD);
  for (int i = lane; i < kD; i += 32) { const float d = __bfloat162float(xr[i]) - mean; q = fmaf(d, d, q); }
  for (int o = 16; o > 0; o >>= 1) q += __shfl_xor_sync(0xffffffffu, q, o);
  const float den = bf16r(sqrtf(bf16r(bf16r(q * (1.0f / kD)) + 1e-5f)));
  for (int i = lane; i < kD; i += 32) xn[blockIdx.x * kD + i] = bf16r(bf16r(__bfloat162float(xr[i]) - bf16r(mean)) / den);
}
__global__ void fb_gemv(const float* a, const float* a2, const __nv_bfloat16* w, float* o, int K, int N) {
  const int n = blockIdx.x * 64 + threadIdx.x, b = blockIdx.y;
  float s = 0.f;
  for (int k = 0; k < K; k++) {
    const float v = a2 ? bf16r(bf16r(silu_f(a[b * K + k])) * a2[b * K + k]) : a[b * K + k];
    s = fmaf(v, __bfloat162float(w[(size_t)k * N + n]), s);
  }
  o[b * N + n] = bf16r(s);
}
__global__ void fb_att(const float* q, const __nv_bfloat16* kc, const __nv_bfloat16* vc, float* o) {
  __shared__ float sm_[8][132];
  const int warp = threadIdx.x >> 5, lane = threadIdx.x & 31;
  const size_t base = (size_t)(blockIdx.x >> 1) * kSK * 128 + lane * 4;
  float qv[4], acc[4] = {0.f, 0.f, 0.f, 0.f}, m = -INFINITY, l = 0.f;
  for (int i = 0; i < 4; i++) qv[i] = q[blockIdx.x * 128 + lane * 4 + i];
  for (int j = warp; j < kSK; j += 8) {
    float s = 0.f;
    for (int i = 0; i < 4; i++) s = fmaf(qv[i], __bfloat162float(kc[base + (size_t)j * 128 + i]), s);
    for (int x = 16; x > 0; x >>= 1) s += __shfl_xor_sync(0xffffffffu, s, x);
    s *= 0.08838834764831845f;
    const float mn = fmaxf(m, s), c = __expf(m - mn), pr = __expf(s - mn);
    l = l * c + pr;
    for (int i = 0; i < 4; i++) acc[i] = acc[i] * c + pr * __bfloat162float(vc[base + (size_t)j * 128 + i]);
    m = mn;
  }
  for (int i = 0; i < 4; i++) sm_[warp][lane * 4 + i] = acc[i];
  if (lane == 0) { sm_[warp][128] = m; sm_[warp][129] = l; }
  __syncthreads();
  if (threadIdx.x < 128) {
    float M = -INFINITY, L = 0.f, r = 0.f;
    for (int w = 0; w < 8; w++) M = fmaxf(M, sm_[w][128]);
    for (int w = 0; w < 8; w++) { const float c = __expf(sm_[w][128] - M); L += c * sm_[w][129]; r += c * sm_[w][threadIdx.x]; }
    o[blockIdx.x * 128 + threadIdx.x] = bf16r(r / L);
  }
}
__global__ void fb_out(const __nv_bfloat16* x, const float* s, const float* d, __nv_bfloat16* out) {
  const int i = blockIdx.x * 64 + threadIdx.x;
  out[i] = __float2bfloat16_rn(__bfloat162float(x[i]) + bf16r(s[i] * bf16r(silu_f(d[i]))));
}

typedef CUresult (*EncodeFn)(CUtensorMap*, CUtensorMapDataType, cuuint32_t, void*, const cuuint64_t*,
                             const cuuint64_t*, const cuuint32_t*, const cuuint32_t*, CUtensorMapInterleave,
                             CUtensorMapSwizzle, CUtensorMapL2promotion, CUtensorMapFloatOOBfill);

void encode(EncodeFn fn, CUtensorMap* m, const void* base, int rank, const cuuint64_t* dims, const cuuint64_t* strides,
            const cuuint32_t* box, CUtensorMapSwizzle sw,
            CUtensorMapL2promotion promo = CU_TENSOR_MAP_L2_PROMOTION_L2_128B) {
  const cuuint32_t es[4] = {1, 1, 1, 1};
  fn(m, CU_TENSOR_MAP_DATA_TYPE_BFLOAT16, rank, const_cast<void*>(base), dims, strides, box, es,
     CU_TENSOR_MAP_INTERLEAVE_NONE, sw, promo, CU_TENSOR_MAP_FLOAT_OOB_FILL_NONE);
}

}

extern "C" void kernel_launch(void* const* d_in, const int* in_sizes, int n_in, void* d_out, int out_size) {
  (void)in_sizes; (void)n_in; (void)out_size;
  static EncodeFn fn = nullptr;
  static int sms = 0;
  static Scratch* sc = nullptr;
  if (!sms) {
    void* p = nullptr;
    cudaDriverEntryPointQueryResult qr;
    cudaGetDriverEntryPoint("cuTensorMapEncodeTiled", &p, cudaEnableDefault, &qr);
    fn = (EncodeFn)p;
    int dev = 0;
    cudaGetDevice(&dev);
    cudaDeviceGetAttribute(&sms, cudaDevAttrMultiProcessorCount, dev);
    cudaGetSymbolAddress(&p, g_raw);
    sc = reinterpret_cast<Scratch*>((reinterpret_cast<uintptr_t>(p) + (2u << 20) - 1) & ~(uintptr_t)((2u << 20) - 1));
    cudaFuncSetAttribute(fused_decode_kernel, cudaFuncAttributeMaxDynamicSharedMemorySize, kSmemBytes);
  }
  if (sms < kSliceCtas || !fn) {
    typedef const __nv_bfloat16* P;
    float* t = reinterpret_cast<float*>(sc);
    float *xn = t, *q = t + 8192, *o = q + 32768, *g = o + 32768, *u = g + 36864, *sv = u + 36864, *d = sv + 8192;
    fb_ln<<<kB, 32>>>((P)d_in[0], xn);
    fb_gemv<<<dim3(64, kB), 64>>>(xn, nullptr, (P)d_in[3], q, kD, 4096);
    fb_att<<<256, 256>>>(q, (P)d_in[1], (P)d_in[2], o);
    fb_gemv<<<dim3(9, kB), 64>>>(o, nullptr, (P)d_in[4], sv, 4096, kD);
    fb_gemv<<<dim3(72, kB), 64>>>(xn, nullptr, (P)d_in[6], g, kD, kF);
    fb_gemv<<<dim3(72, kB), 64>>>(xn, nullptr, (P)d_in[7], u, kD, kF);
    fb_gemv<<<dim3(9, kB), 64>>>(g, u, (P)d_in[8], d, kF, kD);
    fb_out<<<72, 64>>>((P)d_in[0], sv, d, (__nv_bfloat16*)d_out);
    return;
  }
  Maps maps;
  {
    const cuuint64_t dims[3] = {64, (cuuint64_t)kPairs * kSK, 2}, str[2] = {256, 128};
    const cuuint32_t box[3] = {64, 32, 2};
    encode(fn, &maps.k, d_in[1], 3, dims, str, box, CU_TENSOR_MAP_SWIZZLE_128B, CU_TENSOR_MAP_L2_PROMOTION_L2_256B);
    encode(fn, &maps.v, d_in[2], 3, dims, str, box, CU_TENSOR_MAP_SWIZZLE_128B, CU_TENSOR_MAP_L2_PROMOTION_L2_256B);
  }
  {
    const cuuint64_t dims[4] = {64, 128, 32, 9}, str[3] = {kD * 2, 128 * kD * 2, 128};
    const cuuint32_t box[4] = {64, 16, 2, 9};
    encode(fn, &maps.wo, d_in[4], 4, dims, str, box, CU_TENSOR_MAP_SWIZZLE_128B);
  }
  {
    const cuuint64_t dims[2] = {kF, kD}, str[1] = {kF * 2};
    const cuuint32_t box[2] = {32, 144};
    encode(fn, &maps.wg, d_in[6], 2, dims, str, box, CU_TENSOR_MAP_SWIZZLE_64B);
    encode(fn, &maps.wu, d_in[7], 2, dims, str, box, CU_TENSOR_MAP_SWIZZLE_64B);
  }
  {
    const cuuint64_t dims[2] = {kD, kF}, str[1] = {kD * 2};
    const cuuint32_t box[2] = {144, 32};
    encode(fn, &maps.wd, d_in[8], 2, dims, str, box, CU_TENSOR_MAP_SWIZZLE_NONE);
  }
  int grid = sms < kMaxCtas ? sms : kMaxCtas;
  fused_decode_kernel<<<grid, kThreads, kSmemBytes>>>((const char*)d_in[3], (const __nv_bfloat16*)d_in[0],
                                                      (__nv_bfloat16*)d_out, sc, maps);
}
```

```cpp
#include <cuda_runtime.h>
#include <cuda_bf16.h>
#include <cuda.h>
#include <stddef.h>
#include <stdint.h>

namespace {

constexpr int kB = 8, kD = 576, kHKV = 16, kSK = 8192, kF = 4608;
constexpr int kPairs = kB * kHKV;
constexpr int kItemRows = 64;
constexpr int kItemsPerPair = kSK / kItemRows;
constexpr int kNAtt = kPairs * kItemsPerPair;
constexpr int kNFfn = kF / 32;
constexpr int kNItems = kNAtt + kNFfn;
constexpr int kPublish = 8;
constexpr int kSlots = 8;
constexpr int kSlotBytes = 16384;
constexpr int kMaxCtas = kNFfn;
constexpr int kSliceCtas = 128;
constexpr int kRow7Ctas = 72;
constexpr int kThreads = 256;
constexpr int kOutElems = kB * kD;

constexpr int kOffRing = 0;
constexpr int kOffW = kOffRing + kSlots * kSlotBytes;
constexpr int kOffXn = kOffW + 36864;
constexpr int kXnPitch = 584;
constexpr int kOffMbuf = kOffXn + kB * kXnPitch * 2;
constexpr int kMbufStride = 264;
constexpr int kOffOs = kOffMbuf + 2 * 4 * kMbufStride * 4;
constexpr int kOffWbuf = kOffOs + 8 * 40 * 2;
constexpr int kOffFsum = kOffWbuf + 2 * 128 * 8;
constexpr int kOffSsum = kOffFsum + 14 * 36 * 4;
constexpr int kOffG7 = kOffSsum + 8 * 36 * 4;
constexpr int kOffCbuf = kOffG7 + 104 * 4;
constexpr int kOffInfo = kOffCbuf + 4 * 40 * 4;
constexpr int kOffBar = kOffInfo + 64;
constexpr int kNumBars = 3 * kSlots + 12 + 6;
constexpr unsigned long long kBarCount4 = 0x600ull << (3 * kSlots);
constexpr unsigned long long kBarCount2 = 0xfull << (3 * kSlots);
constexpr int kSmemBytes = kOffBar + kNumBars * 8 + 1024;
static_assert(kSmemBytes <= 232448, "smem");

constexpr int kPartSlots = 48;
__device__ __forceinline__ int PSLOT(int pair) { return pair >= 112 ? pair - 112 : 16 + (pair & 31); }

struct Counters {
  unsigned claim;
  unsigned qready; unsigned pad1[30];
  unsigned ddone;  unsigned pad2[31];
  unsigned zready; unsigned pad3[31];
  unsigned exitc;  unsigned pad4[31];
  unsigned cons[8 * 32];
  unsigned done[kPairs * 32];
};

struct Scratch {
  Counters ctr;
  alignas(128) __nv_bfloat16 q[kPairs * 256];
  alignas(128) float4 pml[kPartSlots * 8 * kItemsPerPair];
  alignas(128) float s7[kRow7Ctas * kSliceCtas * 8];
  alignas(128) float po[kPartSlots * kItemsPerPair * 256];
  alignas(128) float sp[kSliceCtas * kOutElems];
  alignas(128) float dp[kMaxCtas * kOutElems];
};
__device__ __align__(128) unsigned char g_raw[sizeof(Scratch) + (2u << 20)];

constexpr int kSpinLimit = 1 << 21;

__device__ __forceinline__ uint32_t smem_u32(const void* p) { return (uint32_t)__cvta_generic_to_shared(p); }
__device__ __forceinline__ void mbar_init(uint32_t bar, uint32_t cnt) {
  asm volatile("mbarrier.init.shared::cta.b64 [%0], %1;" ::"r"(bar), "r"(cnt) : "memory");
}
__device__ __forceinline__ void mbar_expect_tx(uint32_t bar, uint32_t bytes) {
  asm volatile("mbarrier.arrive.expect_tx.shared::cta.b64 _, [%0], %1;" ::"r"(bar), "r"(bytes) : "memory");
}
__device__ __forceinline__ void mbar_arrive(uint32_t bar) {
  asm volatile("mbarrier.arrive.shared::cta.b64 _, [%0];" ::"r"(bar) : "memory");
}
__device__ __forceinline__ void mbar_wait(uint32_t bar, uint32_t parity) {
  uint32_t done;
  int it = 0;
  do {
    asm volatile(
        "{\n.reg .pred p;\nmbarrier.try_wait.parity.shared::cta.b64 p, [%1], %2;\nselp.u32 %0, 1, 0, p;\n}"
        : "=r"(done) : "r"(bar), "r"(parity) : "memory");
    if (++it > kSpinLimit) __trap();
  } while (!done);
}
__device__ __forceinline__ bool mbar_test(uint32_t bar, uint32_t parity) {
  uint32_t done;
  asm volatile(
      "{\n.reg .pred p;\nmbarrier.test_wait.parity.shared::cta.b64 p, [%1], %2;\nselp.u32 %0, 1, 0, p;\n}"
      : "=r"(done) : "r"(bar), "r"(parity) : "memory");
  return done != 0;
}
__device__ __forceinline__ void tma2d(uint32_t dst, const CUtensorMap* m, int c0, int c1, uint32_t bar, uint64_t pol) {
  asm volatile(
      "cp.async.bulk.tensor.2d.shared::cluster.global.mbarrier::complete_tx::bytes.L2::cache_hint [%0], [%1, {%3, %4}], [%2], %5;"
      ::"r"(dst), "l"(m), "r"(bar), "r"(c0), "r"(c1), "l"(pol) : "memory");
}
__device__ __forceinline__ void tma3d(uint32_t dst, const CUtensorMap* m, int c0, int c1, int c2, uint32_t bar, uint64_t pol) {
  asm volatile(
      "cp.async.bulk.tensor.3d.shared::cluster.global.mbarrier::complete_tx::bytes.L2::cache_hint [%0], [%1, {%3, %4, %5}], [%2], %6;"
      ::"r"(dst), "l"(m), "r"(bar), "r"(c0), "r"(c1), "r"(c2), "l"(pol) : "memory");
}
__device__ __forceinline__ void tma4d(uint32_t dst, const CUtensorMap* m, int c0, int c1, int c2, int c3, uint32_t bar, uint64_t pol) {
  asm volatile(
      "cp.async.bulk.tensor.4d.shared::cluster.global.mbarrier::complete_tx::bytes.L2::cache_hint [%0], [%1, {%3, %4, %5, %6}], [%2], %7;"
      ::"r"(dst), "l"(m), "r"(bar), "r"(c0), "r"(c1), "r"(c2), "r"(c3), "l"(pol) : "memory");
}
__device__ __forceinline__ void cp_async16(uint32_t dst, const void* src) {
  asm volatile("cp.async.cg.shared.global.L2::128B [%0], [%1], 16;" ::"r"(dst), "l"(src) : "memory");
}
__device__ __forceinline__ void ldsm4(uint32_t (&r)[4], uint32_t addr) {
  asm volatile("ldmatrix.sync.aligned.m8n8.x4.shared.b16 {%0,%1,%2,%3}, [%4];"
               : "=r"(r[0]), "=r"(r[1]), "=r"(r[2]), "=r"(r[3]) : "r"(addr) : "memory");
}
__device__ __forceinline__ void ldsm4t(uint32_t (&r)[4], uint32_t addr) {
  asm volatile("ldmatrix.sync.aligned.m8n8.x4.trans.shared.b16 {%0,%1,%2,%3}, [%4];"
               : "=r"(r[0]), "=r"(r[1]), "=r"(r[2]), "=r"(r[3]) : "r"(addr) : "memory");
}
__device__ __forceinline__ void mma16816(float (&c)[4], const uint32_t (&a)[4], uint32_t b0, uint32_t b1) {
  asm(
      "mma.sync.aligned.m16n8k16.row.col.f32.bf16.bf16.f32 {%0,%1,%2,%3}, {%4,%5,%6,%7}, {%8,%9}, {%0,%1,%2,%3};"
      : "+f"(c[0]), "+f"(c[1]), "+f"(c[2]), "+f"(c[3])
      : "r"(a[0]), "r"(a[1]), "r"(a[2]), "r"(a[3]), "r"(b0), "r"(b1));
}
__device__ __forceinline__ uint32_t movmat(uint32_t a) {
  uint32_t d;
  asm volatile("movmatrix.sync.aligned.m8n8.trans.b16 %0, %1;" : "=r"(d) : "r"(a));
  return d;
}
__device__ __forceinline__ float ex2(float x) {
  float y;
  asm("ex2.approx.ftz.f32 %0, %1;" : "=f"(y) : "f"(x));
  return y;
}
__device__ __forceinline__ uint32_t pack_bf16(float lo, float hi) {
  uint32_t r;
  asm("cvt.rn.bf16x2.f32 %0, %1, %2;" : "=r"(r) : "f"(hi), "f"(lo));
  return r;
}
__device__ __forceinline__ float bf16r(float x) { return __bfloat162float(__float2bfloat16_rn(x)); }
__device__ __forceinline__ float silu_f(float x) { return x / (1.0f + __expf(-x)); }
__device__ __forceinline__ float warp_max(float x) {
  int i = __float_as_int(x);
  i ^= (i >> 31) & 0x7fffffff;
  i = __reduce_max_sync(0xffffffffu, i);
  i ^= (i >> 31) & 0x7fffffff;
  return __int_as_float(i);
}
__device__ __forceinline__ void bar_sync(int id, int n) { asm volatile("bar.sync %0, %1;" ::"r"(id), "r"(n) : "memory"); }
__device__ __forceinline__ void bar_arrive(int id, int n) { asm volatile("bar.arrive %0, %1;" ::"r"(id), "r"(n) : "memory"); }
__device__ __forceinline__ void red_release(unsigned* p, unsigned v) {
  asm volatile("red.release.gpu.global.add.u32 [%0], %1;" ::"l"(p), "r"(v) : "memory");
}
__device__ __forceinline__ void red_relaxed(unsigned* p, unsigned v) {
  asm volatile("red.relaxed.gpu.global.add.u32 [%0], %1;" ::"l"(p), "r"(v) : "memory");
}
__device__ __forceinline__ unsigned ld_acquire(const unsigned* p) {
  unsigned v;
  asm volatile("ld.acquire.gpu.global.u32 %0, [%1];" : "=r"(v) : "l"(p) : "memory");
  return v;
}
__device__ __forceinline__ unsigned atom_add(unsigned* p, unsigned v) {
  unsigned r;
  asm volatile("atom.relaxed.gpu.global.add.u32 %0, [%1], %2;" : "=r"(r) : "l"(p), "r"(v) : "memory");
  return r;
}
__device__ __forceinline__ void poll_ge(const unsigned* p, unsigned target, unsigned sleep_ns) {
  int it = 0;
  while (ld_acquire(p) < target) {
    if (sleep_ns) __nanosleep(sleep_ns);
    if (++it > kSpinLimit) __trap();
  }
}
__device__ __forceinline__ float4 ldx4(const float* p) {
  float4 v;
  asm volatile("ld.relaxed.gpu.global.v4.f32 {%0,%1,%2,%3}, [%4];" : "=f"(v.x), "=f"(v.y), "=f"(v.z), "=f"(v.w) : "l"(p) : "memory");
  return v;
}
__device__ __forceinline__ float nz(float v) { return __float_as_uint(v) == 0u ? -0.0f : v; }
__device__ __forceinline__ void stx4(float* p, float4 v) {
  asm volatile("st.relaxed.gpu.global.v4.f32 [%0], {%1,%2,%3,%4};" ::"l"(p), "f"(nz(v.x)), "f"(nz(v.y)), "f"(nz(v.z)), "f"(nz(v.w)) : "memory");
}
__device__ __forceinline__ void stx2(float* p, float a, float b) {
  asm volatile("st.relaxed.gpu.global.v2.f32 [%0], {%1,%2};" ::"l"(p), "f"(nz(a)), "f"(nz(b)) : "memory");
}
__device__ __forceinline__ void stx1(float* p, float a) {
  asm volatile("st.relaxed.gpu.global.f32 [%0], %1;" ::"l"(p), "f"(nz(a)) : "memory");
}
__device__ __forceinline__ void clr4(float* p) {
  asm volatile("st.relaxed.gpu.global.v4.f32 [%0], {%1,%1,%1,%1};" ::"l"(p), "f"(0.0f) : "memory");
}
__device__ __forceinline__ bool full4(const float4& v) {
  return __float_as_uint(v.x) != 0u && __float_as_uint(v.y) != 0u && __float_as_uint(v.z) != 0u && __float_as_uint(v.w) != 0u;
}
__device__ __forceinline__ void load_wo(uint32_t (&a)[18][4], uint32_t base, int w, int lane) {
  const uint32_t wl = ((lane & 7) + (lane >> 4) * 8) * 128 + ((((lane >> 3) & 1) ^ (lane & 7)) << 4);
#pragma unroll
  for (int mt = 0; mt < 9; mt++) {
    const int tile = w * 9 + mt;
    const uint32_t ad = base + (tile >> 2) * 4096 + (wl ^ ((tile & 3) << 5));
    ldsm4t(a[2 * mt], ad);
    ldsm4t(a[2 * mt + 1], ad + 2048);
  }
}

struct Maps {
  CUtensorMap wg, wu, wd, k, v, wo;
};

__global__ void __launch_bounds__(kThreads, 1)
fused_decode_kernel(const char* __restrict__ wqp, const __nv_bfloat16* __restrict__ x,
                    __nv_bfloat16* __restrict__ out, Scratch* sc, const __grid_constant__ Maps maps) {
  if (threadIdx.x == 224 && blockIdx.x < kSliceCtas)
    asm volatile("cp.async.bulk.prefetch.L2.global [%0], %1;" ::"l"(wqp + (size_t)blockIdx.x * 36864), "r"(36864) : "memory");
  extern __shared__ unsigned char smem_dyn[];
  unsigned char* sm = smem_dyn + ((1024u - (smem_u32(smem_dyn) & 1023u)) & 1023u);
  const uint32_t sb = smem_u32(sm);
  const int tid = threadIdx.x, warp = tid >> 5, lane = tid & 31;
  const int cta = blockIdx.x, G = gridDim.x;
  const uint32_t barFull = sb + kOffBar, barEmpty = barFull + kSlots * 8, barInfo = barEmpty + kSlots * 8;
  const uint32_t barMfull = barInfo + kSlots * 8, barMempty = barMfull + 32;
  const uint32_t barWo = barMempty + 32, barD = barWo + 8, barQ = barD + 8, barQok = barQ + 8;
  const uint32_t barFree = barQok + 8;
  volatile int* info = reinterpret_cast<volatile int*>(sm + kOffInfo);
  constexpr int kLastBatch = kNAtt - kHKV * kItemsPerPair;

  uint2 xr[9];
  if (warp < 4) {
    const uint2* xp = reinterpret_cast<const uint2*>(x + (warp * 2 + (lane >> 4)) * kD) + (lane & 15);
#pragma unroll
    for (int i = 0; i < 9; i++) xr[i] = __ldg(xp + i * 16);
    if (cta < kSliceCtas) {
      const uint32_t dst = sb + kOffW + warp * 9216 + (lane >> 2) * 64 + (((lane & 3) ^ ((lane >> 3) & 3)) << 4);
      const char* src = wqp + (size_t)(warp * 144 + (lane >> 2)) * 8192 + cta * 64 + (lane & 3) * 16;
#pragma unroll 1
      for (int i = 0; i < 18; i++) cp_async16(dst + i * 512, src + (size_t)i * 65536);
      asm volatile("cp.async.commit_group;" ::: "memory");
    }
  }
  if (warp == 5 && lane < 6)
    asm volatile("prefetch.tensormap [%0];" ::"l"(reinterpret_cast<const CUtensorMap*>(&maps) + lane) : "memory");
  unsigned nextDyn = 0;
  uint64_t pol = 0;
  if (tid == 128) {
    nextDyn = atom_add(&sc->ctr.claim, 1);
#pragma unroll
    for (int i = 0; i < kNumBars; i++) mbar_init(barFull + i * 8, ((kBarCount4 >> i) & 1) ? 4 : (((kBarCount2 >> i) & 1) ? 2 : 1));
    asm volatile("fence.mbarrier_init.release.cluster;" ::: "memory");
    asm volatile("createpolicy.fractional.L2::evict_first.b64 %0, 1.0;" : "=l"(pol));
#pragma unroll 1
    for (int w = 0; w < kSlots; w++) {
      info[w] = cta;
      mbar_arrive(barInfo + w * 8);
      mbar_expect_tx(barFull + w * 8, 9216);
      tma2d(sb + kOffRing + w * kSlotBytes, &maps.wg + (w >> 2), cta * 32, (w & 3) * 144, barFull + w * 8, pol);
    }
  }
  __syncthreads();

  if (warp >= 4) {
  if (warp == 4) {
    if (lane == 0) {
      int item = cta, n = kSlots;
      while (true) {
        const int nsub = item < kNFfn ? 12 : (item < kNItems ? 2 : 4);
#pragma unroll 1
        for (int w = item == cta ? kSlots : 0; w < nsub; w++, n++) {
          const int slot = n & (kSlots - 1);
          mbar_wait(barEmpty + slot * 8, ((n / kSlots) & 1) ^ 1);
          info[slot] = item;
          mbar_arrive(barInfo + slot * 8);
          const uint32_t fb = barFull + slot * 8;
          const uint32_t dst = sb + kOffRing + slot * kSlotBytes;
          if (item >= kNFfn) {
            if (item < kNItems) {
              mbar_expect_tx(fb, kSlotBytes);
              const int row = (item - kNFfn) * kItemRows + w * 32;
              tma3d(dst, &maps.k, 0, row, 0, fb, pol);
              tma3d(dst + 8192, &maps.v, 0, row, 0, fb, pol);
            }
          } else {
            mbar_expect_tx(fb, 9216);
            const int c = (w & 3) * 144;
            if (w < 8) tma2d(dst, w < 4 ? &maps.wg : &maps.wu, item * 32, c, fb, pol);
            else tma2d(dst, &maps.wd, c, item * 32, fb, pol);
          }
        }
        if (item >= kNItems) break;
        if (item + G < kNFfn) {
          item += G;
          continue;
        }
        item = (int)nextDyn + kNFfn;
        if (item < kNItems) nextDyn = atom_add(&sc->ctr.claim, 1);
      }
      if (cta < kSliceCtas) {
        mbar_wait(barFull + ((n - 6) & (kSlots - 1)) * 8, ((n - 6) / kSlots) & 1);
        mbar_expect_tx(barWo, 36864);
        tma4d(sb + kOffW, &maps.wo, 0, (cta & 7) * 16, (cta >> 3) * 2, 0, barWo, pol);
      }
    }
  } else if (warp == 5) {
    const float* mb = reinterpret_cast<const float*>(sm + kOffMbuf);
    int pend = 0, npend = 0;
    int batch = 0;
    if (lane == 0) {
      if (cta < kSliceCtas) {
        mbar_wait(barQ, 0);
        red_release(&sc->ctr.qready, 1);
      }
      poll_ge(&sc->ctr.qready, kSliceCtas, 50);
      mbar_arrive(barQok);
    }
    __syncwarp();
    for (int kk = 0;; kk++) {
      const int buf = kk & 3;
      mbar_wait(barMfull + buf * 8, (kk >> 2) & 1);
      const float* p = mb + buf * 2 * kMbufStride;
      const int item = __float_as_int(p[260]);
      const int group = item >= kLastBatch - 8 * kItemsPerPair ? 3 : kPublish;
      if (npend >= group || (npend > 0 && (item >> 11) != batch)) {
        if (lane < npend) red_release(&sc->ctr.done[pend * 32], 1);
        npend = 0;
      }
      if (item < 0) break;
      if ((item >> 11) != batch) {
        batch = item >> 11;
        if (batch >= 2) mbar_wait(barFree + (batch - 2) * 8, 0);
      }
      float4 ml[2];
#pragma unroll
      for (int w = 0; w < 2; w++) ml[w] = *reinterpret_cast<const float4*>(p + w * kMbufStride + 256);
      const float M0 = fmaxf(ml[0].x, ml[1].x), M1 = fmaxf(ml[0].z, ml[1].z);
      float4 a = make_float4(0.f, 0.f, 0.f, 0.f), b = a;
      float L0 = 0.f, L1 = 0.f;
#pragma unroll
      for (int w = 0; w < 2; w++) {
        const float s0 = ex2(ml[w].x - M0), s1 = ex2(ml[w].z - M1);
        L0 = fmaf(s0, ml[w].y, L0);
        L1 = fmaf(s1, ml[w].w, L1);
        const float4 u = *reinterpret_cast<const float4*>(p + w * kMbufStride + lane * 4);
        const float4 v = *reinterpret_cast<const float4*>(p + w * kMbufStride + 128 + lane * 4);
        a.x = fmaf(s0, u.x, a.x); a.y = fmaf(s1, u.y, a.y); a.z = fmaf(s0, u.z, a.z); a.w = fmaf(s1, u.w, a.w);
        b.x = fmaf(s0, v.x, b.x); b.y = fmaf(s1, v.y, b.y); b.z = fmaf(s0, v.z, b.z); b.w = fmaf(s1, v.w, b.w);
      }
      float* dst = sc->po + (size_t)PSLOT(item >> 7) * (kItemsPerPair * 256) + (item & 127) * 256;
      stx4(dst + lane * 4, a);
      stx4(dst + 128 + lane * 4, b);
      if (lane < 8)
        stx4(reinterpret_cast<float*>(sc->pml + (PSLOT(item >> 7) * 8 + lane) * kItemsPerPair + (item & 127)), make_float4(M0, L0, M1, L1));
      __syncwarp();
      if (lane == 0) mbar_arrive(barMempty + buf * 8);
      if (item < kLastBatch) {
        if (lane == npend) pend = item >> 7;
        npend++;
      }
    }
  } else {
    const int cw = warp - 6;
    const int ci64 = tid - 192;
    mbar_wait(barQok, 0);
    if (ci64 == 0) {
      mbar_wait(barD, 0);
      red_release(&sc->ctr.ddone, 1);
    }
    if (cta < kSliceCtas) {
      if (lane == 0) poll_ge(&sc->ctr.ddone, G, 500);
      __syncwarp();
      float* ssum = reinterpret_cast<float*>(sm + kOffSsum);
      if (ci64 < 63) {
        const int q = ci64 % 9, pg = ci64 / 9;
        float4 acc = make_float4(0.f, 0.f, 0.f, 0.f);
#pragma unroll 4
        for (int p = pg; p < G; p += 7) {
          const float4 v = ldx4(sc->dp + p * kOutElems + cta * 36 + q * 4);
          acc.x += v.x; acc.y += v.y; acc.z += v.z; acc.w += v.w;
        }
        *reinterpret_cast<float4*>(ssum + pg * 36 + q * 4) = acc;
      }
      float* g7 = reinterpret_cast<float*>(sm + kOffG7);
      if (cta < kRow7Ctas) {
        float acc = 0.f;
#pragma unroll 4
        for (int p = ci64 >> 3; p < G; p += 8) acc += __ldcg(sc->dp + p * kOutElems + (cta * 8 + (ci64 & 7)) * 8 + 7);
        g7[ci64] = acc;
      }
      bar_sync(2, 64);
      if (cta < kRow7Ctas && ci64 >= 56) {
        float d = 0.f;
#pragma unroll
        for (int k = 0; k < 8; k++) d += g7[k * 8 + (ci64 & 7)];
        g7[64 + (ci64 & 7)] = bf16r(silu_f(bf16r(d)));
      }
      if (ci64 < 36) {
        float d = 0.f;
#pragma unroll
        for (int k = 0; k < 7; k++) d += ssum[k * 36 + ci64];
        ssum[252 + ci64] = bf16r(silu_f(bf16r(d)));
      }
      const int kvh = cta >> 3, sl = cta & 7;
      float2* wbuf = reinterpret_cast<float2*>(sm + kOffWbuf) + cw * 128;
      __nv_bfloat16* os = reinterpret_cast<__nv_bfloat16*>(sm + kOffOs);
      const int ci = lane >> 3, q4 = lane & 7;
#pragma unroll 1
      for (int b = cw; b < kB; b += 2) {
        const int pair = b * kHKV + kvh;
        if (b == 4 + cw) {
#pragma unroll 2
          for (int k = 0; k < 18; k++) clr4(sc->sp + cta * kOutElems + (k * 64 + ci64) * 4);
          const int pair7 = PSLOT(7 * kHKV + kvh);
#pragma unroll 2
          for (int k = 0; k < 16; k++)
            clr4(sc->po + ((size_t)pair7 * kItemsPerPair + k * 8 + (ci64 >> 3)) * 256 + sl * 32 + (ci64 & 7) * 4);
          clr4(reinterpret_cast<float*>(sc->pml + (pair7 * 8 + sl) * kItemsPerPair + ci64));
          clr4(reinterpret_cast<float*>(sc->pml + (pair7 * 8 + sl) * kItemsPerPair + 64 + ci64));
          if (cta < kRow7Ctas) {
#pragma unroll
            for (int k = 0; k < 4; k++) clr4(sc->s7 + cta * 1024 + (k * 64 + ci64) * 4);
          }
          __syncwarp();
          if (lane == 0) red_release(&sc->ctr.zready, 1);
        }
        if (b >= 2 && lane == 0) {
          if (b == 7) poll_ge(&sc->ctr.zready, kSliceCtas * 2, 200);
          else poll_ge(&sc->ctr.cons[(b - 2) * 32], kSliceCtas, 200);
          mbar_arrive(barFree + (b - 2) * 8);
        }
        if (b == 7) break;
        const float* pml = reinterpret_cast<const float*>(sc->pml + (PSLOT(pair) * 8 + sl) * kItemsPerPair);
        if (lane == 0) poll_ge(&sc->ctr.done[pair * 32], kItemsPerPair, b == 6 ? 100 : 300);
        __syncwarp();
        const float* po = sc->po + (size_t)PSLOT(pair) * kItemsPerPair * 256 + sl * 32 + q4 * 4 + ci * 256;
        float4 ml[4], v[16];
#pragma unroll
        for (int k = 0; k < 4; k++) ml[k] = ldx4(pml + (k * 32 + lane) * 4);
#pragma unroll
        for (int k = 0; k < 16; k++) v[k] = ldx4(po + k * 1024);
        const float M0 = warp_max(fmaxf(fmaxf(ml[0].x, ml[1].x), fmaxf(ml[2].x, ml[3].x)));
        const float M1 = warp_max(fmaxf(fmaxf(ml[0].z, ml[1].z), fmaxf(ml[2].z, ml[3].z)));
        float L0 = 0.f, L1 = 0.f;
#pragma unroll
        for (int k = 0; k < 4; k++) {
          const float w0 = ex2(ml[k].x - M0), w1 = ex2(ml[k].z - M1);
          L0 = fmaf(w0, ml[k].y, L0);
          L1 = fmaf(w1, ml[k].w, L1);
          wbuf[k * 32 + lane] = make_float2(w0, w1);
        }
        __syncwarp();
        float4 acc = make_float4(0.f, 0.f, 0.f, 0.f);
#pragma unroll 1
        for (int half = 0; half < 2; half++) {
#pragma unroll
          for (int k = 0; k < 16; k++) {
            const float2 w2 = wbuf[half * 64 + k * 4 + ci];
            acc.x = fmaf(w2.x, v[k].x, acc.x); acc.y = fmaf(w2.y, v[k].y, acc.y);
            acc.z = fmaf(w2.x, v[k].z, acc.z); acc.w = fmaf(w2.y, v[k].w, acc.w);
          }
          if (half == 0) {
#pragma unroll
            for (int k = 0; k < 16; k++) v[k] = ldx4(po + (16 + k) * 1024);
          }
        }
        __syncwarp();
        if (lane == 0 && b < 5) red_release(&sc->ctr.cons[b * 32], 1);
#pragma unroll
        for (int o = 1; o <= 16; o <<= 1) {
          L0 += __shfl_xor_sync(0xffffffffu, L0, o);
          L1 += __shfl_xor_sync(0xffffffffu, L1, o);
          if (o >= 8) {
            acc.x += __shfl_xor_sync(0xffffffffu, acc.x, o); acc.y += __shfl_xor_sync(0xffffffffu, acc.y, o);
            acc.z += __shfl_xor_sync(0xffffffffu, acc.z, o); acc.w += __shfl_xor_sync(0xffffffffu, acc.w, o);
          }
        }
        if (lane < 8) {
          const float r0 = 1.0f / L0, r1 = 1.0f / L1;
          *reinterpret_cast<uint32_t*>(os + b * 40 + q4 * 2) = pack_bf16(acc.x * r0, acc.z * r0);
          *reinterpret_cast<uint32_t*>(os + b * 40 + 16 + q4 * 2) = pack_bf16(acc.y * r1, acc.w * r1);
        }
        __syncwarp();
      }
      __syncwarp();
      if (cta < kRow7Ctas) bar_arrive(4, 192);
    } else if (lane == 0) {
      for (int b = 2 + cw; b < kB; b += 2) {
        if (b == 7) poll_ge(&sc->ctr.zready, kSliceCtas * 2, 500);
        else poll_ge(&sc->ctr.cons[(b - 2) * 32], kSliceCtas, 500);
        mbar_arrive(barFree + (b - 2) * 8);
      }
    }
  }
    __syncwarp();
    if (cta < kSliceCtas) {
      const int aw = warp - 4, at = tid - 128;
      const int g = lane >> 2, t = lane & 3;
      const int oe = cta * 36 + at;
      float xv = 0.f;
      if (at < 36) xv = __bfloat162float(x[(oe & 7) * kD + (oe >> 3)]);
      mbar_wait(barFree + 5 * 8, 0);
      mbar_wait(barWo, 0);
      uint32_t a[18][4];
      load_wo(a, sb + kOffW, aw, lane);
      bar_sync(3, 128);
      uint32_t ob[4] = {0u, 0u, 0u, 0u};
      if (g < 7) {
        const __nv_bfloat16* os = reinterpret_cast<const __nv_bfloat16*>(sm + kOffOs) + g * 40 + t * 2;
#pragma unroll
        for (int j = 0; j < 4; j++) ob[j] = *reinterpret_cast<const uint32_t*>(os + j * 8);
      }
#pragma unroll
      for (int mt = 0; mt < 9; mt++) {
        float c[4] = {0.f, 0.f, 0.f, 0.f};
        mma16816(c, a[2 * mt], ob[0], ob[1]);
        mma16816(c, a[2 * mt + 1], ob[2], ob[3]);
#pragma unroll
        for (int h = 0; h < 2; h++) {
          const int e = ((mt * 2 + h) * 8 + g) * 8 + t * 2, u = e / 36;
          stx2(sc->sp + ((aw * 32 + u) * kSliceCtas + cta) * 36 + (e - u * 36), c[2 * h], c[2 * h + 1]);
        }
      }
      bar_sync(5, 256);
      const float* fp = sc->sp + cta * kOutElems + at * 4;
      const int fcnt = at < 18 ? 10 : (at < 126 ? 9 : 0);
      float4 f[10];
#pragma unroll
      for (int k = 0; k < 10; k++) f[k] = k < fcnt ? ldx4(fp + k * 504) : make_float4(-0.f, -0.f, -0.f, -0.f);
      for (int it = 0;; it++) {
        bool ok = true;
#pragma unroll
        for (int k = 0; k < 10; k++) ok = ok && full4(f[k]);
        if (__all_sync(0xffffffffu, ok)) break;
        if (it > kSpinLimit) __trap();
        __nanosleep(40);
#pragma unroll
        for (int k = 0; k < 10; k++)
          if (!full4(f[k])) f[k] = ldx4(fp + k * 504);
      }
      float* fsum = reinterpret_cast<float*>(sm + kOffFsum);
      float4 acc = f[0];
#pragma unroll
      for (int k = 1; k < 10; k++) { acc.x += f[k].x; acc.y += f[k].y; acc.z += f[k].z; acc.w += f[k].w; }
      if (at < 126) *reinterpret_cast<float4*>(fsum + at * 4) = acc;
      bar_sync(3, 128);
      if (at < 36 && (oe & 7) != 7) {
        float s = 0.f;
#pragma unroll
        for (int k = 0; k < 14; k++) s += fsum[k * 36 + at];
        const float gt = reinterpret_cast<const float*>(sm + kOffSsum)[252 + at];
        out[(oe & 7) * kD + (oe >> 3)] = __float2bfloat16_rn(xv + bf16r(bf16r(s) * gt));
      }
    }
  } else {
    const int g = lane >> 2, t = lane & 3;
    __nv_bfloat16* xn = reinterpret_cast<__nv_bfloat16*>(sm + kOffXn);
    {
      float v[36];
#pragma unroll
      for (int i = 0; i < 9; i++) {
        v[4 * i] = __uint_as_float(xr[i].x << 16);
        v[4 * i + 1] = __uint_as_float(xr[i].x & 0xffff0000u);
        v[4 * i + 2] = __uint_as_float(xr[i].y << 16);
        v[4 * i + 3] = __uint_as_float(xr[i].y & 0xffff0000u);
      }
      float s = 0.f;
#pragma unroll
      for (int i = 0; i < 36; i++) s += v[i];
#pragma unroll
      for (int o = 8; o > 0; o >>= 1) s += __shfl_xor_sync(0xffffffffu, s, o);
      const float mean = s * (1.0f / kD);
      float q = 0.f;
#pragma unroll
      for (int i = 0; i < 36; i++) { const float d = v[i] - mean; q = fmaf(d, d, q); }
#pragma unroll
      for (int o = 8; o > 0; o >>= 1) q += __shfl_xor_sync(0xffffffffu, q, o);
      const float mb = bf16r(mean);
      const float rden = 1.0f / bf16r(sqrtf(bf16r(bf16r(q * (1.0f / kD)) + 1e-5f)));
      __nv_bfloat16* xw = xn + (warp * 2 + (lane >> 4)) * kXnPitch + (lane & 15) * 4;
#pragma unroll
      for (int i = 0; i < 9; i++)
        *reinterpret_cast<uint2*>(xw + i * 64) =
            make_uint2(pack_bf16(bf16r(v[4 * i] - mb) * rden, bf16r(v[4 * i + 1] - mb) * rden),
                       pack_bf16(bf16r(v[4 * i + 2] - mb) * rden, bf16r(v[4 * i + 3] - mb) * rden));
    }
    bar_sync(1, 128);
    float* mb = reinterpret_cast<float*>(sm + kOffMbuf);
    const uint32_t r8 = lane & 7;
    const uint32_t guLane = (r8 + (lane >> 4) * 8) * 64 + ((((lane >> 3) & 1) ^ (r8 >> 1)) << 4);
    int slot = warp, item;
    uint32_t fph = 0;
    {
      uint32_t xb[9][2];
#pragma unroll
      for (int ks = 0; ks < 9; ks++) {
        xb[ks][0] = *reinterpret_cast<const uint32_t*>(xn + g * kXnPitch + warp * 144 + ks * 16 + t * 2);
        xb[ks][1] = *reinterpret_cast<const uint32_t*>(xn + g * kXnPitch + warp * 144 + ks * 16 + 8 + t * 2);
      }
      if (cta < kSliceCtas) {
        if (tid == 0) {
          sc->ctr.done[cta * 32] = 0;
          if (cta < 8) sc->ctr.cons[cta * 32] = 0;
          if (cta == 0) { sc->ctr.ddone = 0; sc->ctr.zready = 0; sc->ctr.exitc = 0; }
        }
        asm volatile("cp.async.wait_group 0;" ::: "memory");
        __syncwarp();
        const uint32_t lo = sb + kOffW + warp * 9216;
        uint32_t a[18][4];
#pragma unroll
        for (int i = 0; i < 18; i++) ldsm4t(a[i], lo + (guLane ^ ((i & 1) * 32)) + (i >> 1) * 1024);
        float c[2][4] = {{0.f, 0.f, 0.f, 0.f}, {0.f, 0.f, 0.f, 0.f}};
#pragma unroll
        for (int i = 0; i < 18; i++) mma16816(c[i & 1], a[i], xb[i >> 1][0], xb[i >> 1][1]);
        float* qr = mb + warp * 256;
#pragma unroll
        for (int mt = 0; mt < 2; mt++) {
          *reinterpret_cast<float2*>(qr + (mt * 16 + g) * 8 + t * 2) = make_float2(c[mt][0], c[mt][1]);
          *reinterpret_cast<float2*>(qr + (mt * 16 + 8 + g) * 8 + t * 2) = make_float2(c[mt][2], c[mt][3]);
        }
        bar_sync(1, 128);
        const int b = tid >> 4, cp = tid & 15;
        float q0 = 0.f, q1 = 0.f;
#pragma unroll
        for (int w = 0; w < 4; w++) {
          q0 += mb[w * 256 + (cp * 2) * 8 + b];
          q1 += mb[w * 256 + (cp * 2 + 1) * 8 + b];
        }
        const int col = cta * 32 + cp * 2;
        const int head = col >> 7, d = col & 127;
        const int pos = (head & 1) * 128 + (d >> 5) * 32 + ((d & 7) >> 1) * 8 + ((d >> 4) & 1) * 4 + ((d >> 3) & 1) * 2;
        *reinterpret_cast<uint32_t*>(sc->q + (b * kHKV + (head >> 1)) * 256 + pos) = pack_bf16(q0, q1);
        __syncwarp();
        if (lane == 0) mbar_arrive(barQ);
      } else {
        bar_sync(1, 128);
      }

      float dacc[9][4];
#pragma unroll
      for (int i = 0; i < 9; i++) dacc[i][0] = dacc[i][1] = dacc[i][2] = dacc[i][3] = 0.f;
      float* red = reinterpret_cast<float*>(sm + kOffXn);
      const uint32_t dnLane = (r8 + (lane >> 4) * 8) * 288 + ((lane >> 3) & 1) * 16;
      while (true) {
        mbar_wait(barInfo + slot * 8, fph);
        item = info[slot];
        if (item >= kNFfn) break;
        uint32_t a[18][4];
        float* rw = red + warp * 512;
#pragma unroll 1
        for (int gu = 0; gu < 2; gu++) {
          mbar_wait(barFull + slot * 8, fph);
          const uint32_t base = sb + kOffRing + slot * kSlotBytes;
#pragma unroll
          for (int i = 0; i < 18; i++) ldsm4t(a[i], base + (guLane ^ ((i & 1) * 32)) + (i >> 1) * 1024);
          float c[2][4] = {{0.f, 0.f, 0.f, 0.f}, {0.f, 0.f, 0.f, 0.f}};
#pragma unroll
          for (int i = 0; i < 18; i++) mma16816(c[i & 1], a[i], xb[i >> 1][0], xb[i >> 1][1]);
#pragma unroll
          for (int mt = 0; mt < 2; mt++) {
            float* r = rw + gu * 256 + (2 * t) * 32 + mt * 16 + g;
            r[0] = c[mt][0]; r[32] = c[mt][1]; r[8] = c[mt][2]; r[40] = c[mt][3];
          }
          __syncwarp();
          if (lane == 0) mbar_arrive(barEmpty + slot * 8);
          slot += 4;
          if (slot >= kSlots) { slot -= kSlots; fph ^= 1; }
        }
        bar_sync(1, 128);
        uint32_t hb[4];
#pragma unroll
        for (int j = 0; j < 4; j++) {
          float2 gs = make_float2(0.f, 0.f), us = gs;
#pragma unroll
          for (int w = 0; w < 4; w++) {
            const float* rr = red + w * 512 + g * 32 + j * 8 + t * 2;
            const float2 a2 = *reinterpret_cast<const float2*>(rr), b2 = *reinterpret_cast<const float2*>(rr + 256);
            gs.x += a2.x; gs.y += a2.y; us.x += b2.x; us.y += b2.y;
          }
          hb[j] = pack_bf16(bf16r(silu_f(bf16r(gs.x))) * bf16r(us.x), bf16r(silu_f(bf16r(gs.y))) * bf16r(us.y));
        }
        mbar_wait(barFull + slot * 8, fph);
        const uint32_t base = sb + kOffRing + slot * kSlotBytes + dnLane;
#pragma unroll
        for (int i = 0; i < 18; i++) ldsm4t(a[i], base + (i >> 1) * 32 + (i & 1) * 4608);
#pragma unroll
        for (int i = 0; i < 18; i++) mma16816(dacc[i >> 1], a[i], hb[(i & 1) * 2], hb[(i & 1) * 2 + 1]);
        bar_sync(1, 128);
        if (lane == 0) mbar_arrive(barEmpty + slot * 8);
        slot += 4;
        if (slot >= kSlots) { slot -= kSlots; fph ^= 1; }
      }
      float* dp = sc->dp + cta * kOutElems + (warp * 144 + g) * 8 + t * 2;
#pragma unroll
      for (int mt = 0; mt < 9; mt++) {
        *reinterpret_cast<float2*>(dp + mt * 128) = make_float2(dacc[mt][0], dacc[mt][1]);
        *reinterpret_cast<float2*>(dp + mt * 128 + 64) = make_float2(dacc[mt][2], dacc[mt][3]);
      }
      __syncwarp();
      if (lane == 0) mbar_arrive(barD);
      mbar_wait(barQok, 0);
    }

    const float kScale = 0.08838834764831845f * 1.4426950408889634f;
    const uint32_t kLane = (r8 + ((lane >> 3) & 1) * 8) * 128 + (((lane >> 4) ^ r8) << 4);
    const uint32_t vLane = 8192 + (r8 + (lane >> 4) * 8) * 128 + ((((lane >> 3) & 1) ^ r8) << 4);
    int kk = 0;
    while (item < kNItems) {
      item -= kNFfn;
      uint4 qv[4];
      if (g < 2) {
        const uint4* qs = reinterpret_cast<const uint4*>(sc->q + (item >> 7) * 256 + g * 128 + t * 8);
#pragma unroll
        for (int i = 0; i < 4; i++) qv[i] = qs[i * 4];
      } else {
#pragma unroll
        for (int i = 0; i < 4; i++) qv[i] = make_uint4(0u, 0u, 0u, 0u);
      }
      mbar_wait(barFull + slot * 8, fph);
      const uint32_t base = sb + kOffRing + slot * kSlotBytes;
      uint32_t ka[16][4], va[16][4];
#pragma unroll
      for (int i = 0; i < 16; i++)
        ldsm4(ka[i], base + ((kLane ^ (((i >> 1) & 3) << 5)) + (i >> 3) * 4096 + (i & 1) * 2048));
#pragma unroll
      for (int i = 0; i < 16; i++)
        ldsm4t(va[i], base + ((vLane ^ (((i >> 1) & 3) << 5)) + (i >> 3) * 4096 + (i & 1) * 2048));
      float s[2][4], s2[2][4];
#pragma unroll
      for (int i = 0; i < 4; i++) s[0][i] = s[1][i] = s2[0][i] = s2[1][i] = 0.f;
#pragma unroll
      for (int kp = 0; kp < 4; kp++) {
        mma16816(s[0], ka[4 * kp], qv[kp].x, qv[kp].y);
        mma16816(s[1], ka[4 * kp + 1], qv[kp].x, qv[kp].y);
        mma16816(s2[0], ka[4 * kp + 2], qv[kp].z, qv[kp].w);
        mma16816(s2[1], ka[4 * kp + 3], qv[kp].z, qv[kp].w);
      }
#pragma unroll
      for (int i = 0; i < 4; i++) { s[0][i] += s2[0][i]; s[1][i] += s2[1][i]; }
      float m0 = fmaxf(fmaxf(s[0][0], s[0][2]), fmaxf(s[1][0], s[1][2]));
      float m1 = fmaxf(fmaxf(s[0][1], s[0][3]), fmaxf(s[1][1], s[1][3]));
#pragma unroll
      for (int o = 4; o <= 16; o <<= 1) {
        m0 = fmaxf(m0, __shfl_xor_sync(0xffffffffu, m0, o));
        m1 = fmaxf(m1, __shfl_xor_sync(0xffffffffu, m1, o));
      }
      m0 *= kScale; m1 *= kScale;
      float l0 = 0.f, l1 = 0.f;
      uint32_t pb[2][2];
#pragma unroll
      for (int mt = 0; mt < 2; mt++) {
        const float p0 = ex2(fmaf(s[mt][0], kScale, -m0)), p1 = ex2(fmaf(s[mt][1], kScale, -m1));
        const float p2 = ex2(fmaf(s[mt][2], kScale, -m0)), p3 = ex2(fmaf(s[mt][3], kScale, -m1));
        l0 += p0 + p2; l1 += p1 + p3;
        pb[mt][0] = movmat(pack_bf16(p0, p1));
        pb[mt][1] = movmat(pack_bf16(p2, p3));
      }
      float o_[8][4];
#pragma unroll
      for (int j = 0; j < 8; j++) {
        o_[j][0] = o_[j][1] = o_[j][2] = o_[j][3] = 0.f;
        mma16816(o_[j], va[2 * j], pb[0][0], pb[0][1]);
      }
#pragma unroll
      for (int j = 0; j < 8; j++) mma16816(o_[j], va[2 * j + 1], pb[1][0], pb[1][1]);
#pragma unroll
      for (int o = 4; o <= 16; o <<= 1) {
        l0 += __shfl_xor_sync(0xffffffffu, l0, o);
        l1 += __shfl_xor_sync(0xffffffffu, l1, o);
      }
      const int buf = (kk * 2 + (warp >> 1)) & 3;
      mbar_wait(barMempty + buf * 8, ((kk >> 1) & 1) ^ 1);
      float* p = mb + (buf * 2 + (warp & 1)) * kMbufStride;
      if (t == 0) {
#pragma unroll
        for (int j = 0; j < 8; j++) {
          *reinterpret_cast<float2*>(p + (j * 16 + g) * 2) = make_float2(o_[j][0], o_[j][1]);
          *reinterpret_cast<float2*>(p + (j * 16 + 8 + g) * 2) = make_float2(o_[j][2], o_[j][3]);
        }
        if (g == 0) {
          *reinterpret_cast<float4*>(p + 256) = make_float4(m0, l0, m1, l1);
          p[260] = __int_as_float(item);
        }
      }
      __syncwarp();
      if (lane == 0) {
        mbar_arrive(barMfull + buf * 8);
        mbar_arrive(barEmpty + slot * 8);
      }
      kk++;
      slot += 4;
      if (slot >= kSlots) { slot -= kSlots; fph ^= 1; }
      mbar_wait(barInfo + slot * 8, fph);
      item = info[slot];
    }
    {
      const int buf = (kk * 2 + (warp >> 1)) & 3;
      mbar_wait(barMempty + buf * 8, ((kk >> 1) & 1) ^ 1);
      if (lane == 0) {
        mb[(buf * 2 + (warp & 1)) * kMbufStride + 260] = __int_as_float(-1);
        mbar_arrive(barMfull + buf * 8);
        if (warp == 0) red_relaxed(&sc->ctr.exitc, 1);
      }
      __syncwarp();
    }
    if (cta < kSliceCtas) {
      float xv = 0.f;
      if (tid < 8 && cta < kRow7Ctas) xv = __bfloat162float(x[7 * kD + cta * 8 + tid]);
      mbar_wait(barFree + 5 * 8, 0);
      const int ps = PSLOT(7 * kHKV + (cta >> 3)), sl = cta & 7;
      const int ci = lane >> 3, q4 = lane & 7;
      const float* po = sc->po + (ps * kItemsPerPair + warp * 32 + ci) * 256 + sl * 32 + q4 * 4;
      const float* pml = reinterpret_cast<const float*>(sc->pml + (ps * 8 + sl) * kItemsPerPair + warp * 32 + lane);
      float4 v[9];
#pragma unroll
      for (int k = 0; k < 9; k++) v[k] = ldx4(k < 8 ? po + k * 1024 : pml);
      uint32_t a[18][4], ob[4];
      bool haveWo = false;
      for (int it = 0;; it++) {
        if (!haveWo && __all_sync(0xffffffffu, mbar_test(barWo, 0))) {
          load_wo(a, sb + kOffW, warp, lane);
          haveWo = true;
        }
        bool ok = true;
#pragma unroll
        for (int k = 0; k < 9; k++) ok = ok && full4(v[k]);
        if (__all_sync(0xffffffffu, ok) && haveWo) break;
        if (it > kSpinLimit) __trap();
#pragma unroll
        for (int k = 0; k < 9; k++)
          if (!full4(v[k])) v[k] = ldx4(k < 8 ? po + k * 1024 : pml);
      }
      float* cb = reinterpret_cast<float*>(sm + kOffCbuf);
      {
        const float M0 = warp_max(v[8].x), M1 = warp_max(v[8].z);
        const float w0 = ex2(v[8].x - M0), w1 = ex2(v[8].z - M1);
        float L0 = w0 * v[8].y, L1 = w1 * v[8].w;
        float4 acc = make_float4(0.f, 0.f, 0.f, 0.f);
#pragma unroll
        for (int k = 0; k < 8; k++) {
          const float a0 = __shfl_sync(0xffffffffu, w0, k * 4 + ci), a1 = __shfl_sync(0xffffffffu, w1, k * 4 + ci);
          acc.x = fmaf(a0, v[k].x, acc.x); acc.y = fmaf(a1, v[k].y, acc.y);
          acc.z = fmaf(a0, v[k].z, acc.z); acc.w = fmaf(a1, v[k].w, acc.w);
        }
#pragma unroll
        for (int o = 1; o <= 16; o <<= 1) {
          L0 += __shfl_xor_sync(0xffffffffu, L0, o);
          L1 += __shfl_xor_sync(0xffffffffu, L1, o);
          if (o >= 8) {
            acc.x += __shfl_xor_sync(0xffffffffu, acc.x, o); acc.y += __shfl_xor_sync(0xffffffffu, acc.y, o);
            acc.z += __shfl_xor_sync(0xffffffffu, acc.z, o); acc.w += __shfl_xor_sync(0xffffffffu, acc.w, o);
          }
        }
        if (lane < 8) {
          *reinterpret_cast<float2*>(cb + warp * 40 + q4 * 2) = make_float2(acc.x, acc.z);
          *reinterpret_cast<float2*>(cb + warp * 40 + 16 + q4 * 2) = make_float2(acc.y, acc.w);
          if (lane == 0) *reinterpret_cast<float4*>(cb + warp * 40 + 32) = make_float4(M0, L0, M1, L1);
        }
      }
      bar_sync(1, 128);
      {
        float4 ml[4];
#pragma unroll
        for (int w = 0; w < 4; w++) ml[w] = *reinterpret_cast<const float4*>(cb + w * 40 + 32);
        const float M0 = fmaxf(fmaxf(ml[0].x, ml[1].x), fmaxf(ml[2].x, ml[3].x));
        const float M1 = fmaxf(fmaxf(ml[0].z, ml[1].z), fmaxf(ml[2].z, ml[3].z));
        float L0 = 0.f, L1 = 0.f;
        float2 o2[4] = {{0.f, 0.f}, {0.f, 0.f}, {0.f, 0.f}, {0.f, 0.f}};
#pragma unroll
        for (int w = 0; w < 4; w++) {
          const float s0 = ex2(ml[w].x - M0), s1 = ex2(ml[w].z - M1);
          L0 = fmaf(s0, ml[w].y, L0);
          L1 = fmaf(s1, ml[w].w, L1);
#pragma unroll
          for (int j = 0; j < 4; j++) {
            const float2 u = *reinterpret_cast<const float2*>(cb + w * 40 + j * 8 + t * 2);
            o2[j].x = fmaf(j < 2 ? s0 : s1, u.x, o2[j].x);
            o2[j].y = fmaf(j < 2 ? s0 : s1, u.y, o2[j].y);
          }
        }
        const float r0 = __frcp_rn(L0), r1 = __frcp_rn(L1);
#pragma unroll
        for (int j = 0; j < 4; j++) ob[j] = pack_bf16(o2[j].x * (j < 2 ? r0 : r1), o2[j].y * (j < 2 ? r0 : r1));
      }
      {
        float c[10][4];
#pragma unroll
        for (int mt = 0; mt < 9; mt++) {
          c[mt][0] = c[mt][1] = c[mt][2] = c[mt][3] = 0.f;
          mma16816(c[mt], a[2 * mt], ob[0], ob[1]);
          mma16816(c[mt], a[2 * mt + 1], ob[2], ob[3]);
        }
        c[9][0] = c[9][2] = 0.f;
        float* s7 = sc->s7 + ((warp * 18 + t) * kSliceCtas + cta) * 8 + g;
#pragma unroll
        for (int k = 0; k < 5; k++) {
          const float lo = (t & 1) ? c[2 * k][2] : c[2 * k][0], hi = (t & 1) ? c[2 * k + 1][2] : c[2 * k + 1][0];
          if (k < 4 || t < 2) stx1(s7 + k * 4 * kSliceCtas * 8, (t & 2) ? hi : lo);
        }
      }
      bar_arrive(5, 256);
      if (cta < kRow7Ctas) {
        const float* hp = sc->s7 + cta * 1024 + tid * 4;
        float4 f0 = ldx4(hp), f1 = ldx4(hp + 512);
        for (int it = 0; !__all_sync(0xffffffffu, full4(f0) && full4(f1)); it++) {
          if (it > kSpinLimit) __trap();
          if (!full4(f0)) f0 = ldx4(hp);
          if (!full4(f1)) f1 = ldx4(hp + 512);
        }
        float* g7 = reinterpret_cast<float*>(sm + kOffG7);
        float4 h = make_float4(f0.x + f1.x, f0.y + f1.y, f0.z + f1.z, f0.w + f1.w);
#pragma unroll
        for (int o = 2; o <= 16; o <<= 1) {
          h.x += __shfl_xor_sync(0xffffffffu, h.x, o); h.y += __shfl_xor_sync(0xffffffffu, h.y, o);
          h.z += __shfl_xor_sync(0xffffffffu, h.z, o); h.w += __shfl_xor_sync(0xffffffffu, h.w, o);
        }
        if (lane < 2) *reinterpret_cast<float4*>(g7 + 72 + warp * 8 + lane * 4) = h;
        bar_sync(4, 192);
        if (tid < 8) {
          const float s = (g7[72 + tid] + g7[80 + tid]) + (g7[88 + tid] + g7[96 + tid]);
          out[7 * kD + cta * 8 + tid] = __float2bfloat16_rn(xv + bf16r(bf16r(s) * g7[64 + tid]));
        }
      }
      if (cta == 0 && tid == 96) {
        poll_ge(&sc->ctr.exitc, G, 20);
        sc->ctr.claim = 0;
        sc->ctr.qready = 0;
      }
    }
  }
}

__global__ void fb_ln(const __nv_bfloat16* x, float* xn) {
  const int lane = threadIdx.x;
  const __nv_bfloat16* xr = x + blockIdx.x * kD;
  float s = 0.f, q = 0.f;
  for (int i = lane; i < kD; i += 32) s += __bfloat162float(xr[i]);
  for (int o = 16; o > 0; o >>= 1) s += __shfl_xor_sync(0xffffffffu, s, o);
  const float mean = s * (1.0f / kD);
  for (int i = lane; i < kD; i += 32) { const float d = __bfloat162float(xr[i]) - mean; q = fmaf(d, d, q); }
  for (int o = 16; o > 0; o >>= 1) q += __shfl_xor_sync(0xffffffffu, q, o);
  const float den = bf16r(sqrtf(bf16r(bf16r(q * (1.0f / kD)) + 1e-5f)));
  for (int i = lane; i < kD; i += 32) xn[blockIdx.x * kD + i] = bf16r(bf16r(__bfloat162float(xr[i]) - bf16r(mean)) / den);
}
__global__ void fb_gemv(const float* a, const float* a2, const __nv_bfloat16* w, float* o, int K, int N) {
  const int n = blockIdx.x * 64 + threadIdx.x, b = blockIdx.y;
  float s = 0.f;
  for (int k = 0; k < K; k++) {
    const float v = a2 ? bf16r(bf16r(silu_f(a[b * K + k])) * a2[b * K + k]) : a[b * K + k];
    s = fmaf(v, __bfloat162float(w[(size_t)k * N + n]), s);
  }
  o[b * N + n] = bf16r(s);
}
__global__ void fb_att(const float* q, const __nv_bfloat16* kc, const __nv_bfloat16* vc, float* o) {
  __shared__ float sm_[8][132];
  const int warp = threadIdx.x >> 5, lane = threadIdx.x & 31;
  const size_t base = (size_t)(blockIdx.x >> 1) * kSK * 128 + lane * 4;
  float qv[4], acc[4] = {0.f, 0.f, 0.f, 0.f}, m = -INFINITY, l = 0.f;
  for (int i = 0; i < 4; i++) qv[i] = q[blockIdx.x * 128 + lane * 4 + i];
  for (int j = warp; j < kSK; j += 8) {
    float s = 0.f;
    for (int i = 0; i < 4; i++) s = fmaf(qv[i], __bfloat162float(kc[base + (size_t)j * 128 + i]), s);
    for (int x = 16; x > 0; x >>= 1) s += __shfl_xor_sync(0xffffffffu, s, x);
    s *= 0.08838834764831845f;
    const float mn = fmaxf(m, s), c = __expf(m - mn), pr = __expf(s - mn);
    l = l * c + pr;
    for (int i = 0; i < 4; i++) acc[i] = acc[i] * c + pr * __bfloat162float(vc[base + (size_t)j * 128 + i]);
    m = mn;
  }
  for (int i = 0; i < 4; i++) sm_[warp][lane * 4 + i] = acc[i];
  if (lane == 0) { sm_[warp][128] = m; sm_[warp][129] = l; }
  __syncthreads();
  if (threadIdx.x < 128) {
    float M = -INFINITY, L = 0.f, r = 0.f;
    for (int w = 0; w < 8; w++) M = fmaxf(M, sm_[w][128]);
    for (int w = 0; w < 8; w++) { const float c = __expf(sm_[w][128] - M); L += c * sm_[w][129]; r += c * sm_[w][threadIdx.x]; }
    o[blockIdx.x * 128 + threadIdx.x] = bf16r(r / L);
  }
}
__global__ void fb_out(const __nv_bfloat16* x, const float* s, const float* d, __nv_bfloat16* out) {
  const int i = blockIdx.x * 64 + threadIdx.x;
  out[i] = __float2bfloat16_rn(__bfloat162float(x[i]) + bf16r(s[i] * bf16r(silu_f(d[i]))));
}

typedef CUresult (*EncodeFn)(CUtensorMap*, CUtensorMapDataType, cuuint32_t, void*, const cuuint64_t*,
                             const cuuint64_t*, const cuuint32_t*, const cuuint32_t*, CUtensorMapInterleave,
                             CUtensorMapSwizzle, CUtensorMapL2promotion, CUtensorMapFloatOOBfill);

void encode(EncodeFn fn, CUtensorMap* m, const void* base, int rank, const cuuint64_t* dims, const cuuint64_t* strides,
            const cuuint32_t* box, CUtensorMapSwizzle sw,
            CUtensorMapL2promotion promo = CU_TENSOR_MAP_L2_PROMOTION_L2_128B) {
  const cuuint32_t es[4] = {1, 1, 1, 1};
  fn(m, CU_TENSOR_MAP_DATA_TYPE_BFLOAT16, rank, const_cast<void*>(base), dims, strides, box, es,
     CU_TENSOR_MAP_INTERLEAVE_NONE, sw, promo, CU_TENSOR_MAP_FLOAT_OOB_FILL_NONE);
}

}

extern "C" void kernel_launch(void* const* d_in, const int* in_sizes, int n_in, void* d_out, int out_size) {
  (void)in_sizes; (void)n_in; (void)out_size;
  static EncodeFn fn = nullptr;
  static int sms = 0;
  static Scratch* sc = nullptr;
  if (!sms) {
    void* p = nullptr;
    cudaDriverEntryPointQueryResult qr;
    cudaGetDriverEntryPoint("cuTensorMapEncodeTiled", &p, cudaEnableDefault, &qr);
    fn = (EncodeFn)p;
    int dev = 0;
    cudaGetDevice(&dev);
    cudaDeviceGetAttribute(&sms, cudaDevAttrMultiProcessorCount, dev);
    cudaGetSymbolAddress(&p, g_raw);
    sc = reinterpret_cast<Scratch*>((reinterpret_cast<uintptr_t>(p) + (2u << 20) - 1) & ~(uintptr_t)((2u << 20) - 1));
    cudaFuncSetAttribute(fused_decode_kernel, cudaFuncAttributeMaxDynamicSharedMemorySize, kSmemBytes);
  }
  if (sms < kSliceCtas || !fn) {
    typedef const __nv_bfloat16* P;
    float* t = reinterpret_cast<float*>(sc);
    float *xn = t, *q = t + 8192, *o = q + 32768, *g = o + 32768, *u = g + 36864, *sv = u + 36864, *d = sv + 8192;
    fb_ln<<<kB, 32>>>((P)d_in[0], xn);
    fb_gemv<<<dim3(64, kB), 64>>>(xn, nullptr, (P)d_in[3], q, kD, 4096);
    fb_att<<<256, 256>>>(q, (P)d_in[1], (P)d_in[2], o);
    fb_gemv<<<dim3(9, kB), 64>>>(o, nullptr, (P)d_in[4], sv, 4096, kD);
    fb_gemv<<<dim3(72, kB), 64>>>(xn, nullptr, (P)d_in[6], g, kD, kF);
    fb_gemv<<<dim3(72, kB), 64>>>(xn, nullptr, (P)d_in[7], u, kD, kF);
    fb_gemv<<<dim3(9, kB), 64>>>(g, u, (P)d_in[8], d, kF, kD);
    fb_out<<<72, 64>>>((P)d_in[0], sv, d, (__nv_bfloat16*)d_out);
    return;
  }
  Maps maps;
  {
    const cuuint64_t dims[3] = {64, (cuuint64_t)kPairs * kSK, 2}, str[2] = {256, 128};
    const cuuint32_t box[3] = {64, 32, 2};
    encode(fn, &maps.k, d_in[1], 3, dims, str, box, CU_TENSOR_MAP_SWIZZLE_128B, CU_TENSOR_MAP_L2_PROMOTION_L2_256B);
    encode(fn, &maps.v, d_in[2], 3, dims, str, box, CU_TENSOR_MAP_SWIZZLE_128B, CU_TENSOR_MAP_L2_PROMOTION_L2_256B);
  }
  {
    const cuuint64_t dims[4] = {64, 128, 32, 9}, str[3] = {kD * 2, 128 * kD * 2, 128};
    const cuuint32_t box[4] = {64, 16, 2, 9};
    encode(fn, &maps.wo, d_in[4], 4, dims, str, box, CU_TENSOR_MAP_SWIZZLE_128B);
  }
  {
    const cuuint64_t dims[2] = {kF, kD}, str[1] = {kF * 2};
    const cuuint32_t box[2] = {32, 144};
    encode(fn, &maps.wg, d_in[6], 2, dims, str, box, CU_TENSOR_MAP_SWIZZLE_64B);
    encode(fn, &maps.wu, d_in[7], 2, dims, str, box, CU_TENSOR_MAP_SWIZZLE_64B);
  }
  {
    const cuuint64_t dims[2] = {kD, kF}, str[1] = {kD * 2};
    const cuuint32_t box[2] = {144, 32};
    encode(fn, &maps.wd, d_in[8], 2, dims, str, box, CU_TENSOR_MAP_SWIZZLE_NONE);
  }
  int grid = sms < kMaxCtas ? sms : kMaxCtas;
  fused_decode_kernel<<<grid, kThreads, kSmemBytes>>>((const char*)d_in[3], (const __nv_bfloat16*)d_in[0],
                                                      (__nv_bfloat16*)d_out, sc, maps);
}
```
